```python
import torch

def _softmax(x, axis=-1):
    return torch.softmax(x, dim=axis)

def _gelu(x):
    return torch.nn.functional.gelu(x, approximate='tanh')

def _silu(x):
    return torch.nn.functional.silu(x)

def _sigmoid(x):
    return torch.sigmoid(x)

def _layernorm(x, axis=-1, eps=1e-05):
    m = x.mean(dim=axis, keepdim=True)
    v = x.var(dim=axis, keepdim=True, unbiased=False)
    return (x - m) / torch.sqrt(v + eps)

def _scatter_add(tgt, idx, src, axis=0):
    return tgt.clone().index_add_(axis, idx, src)

def _segment_sum(src, seg, n):
    out = torch.zeros((n,) + src.shape[1:], dtype=src.dtype)
    return out.index_add_(0, seg, src)

def _pad(x, pw):
    flat = tuple((v for pair in reversed(pw) for v in pair))
    return torch.nn.functional.pad(x, flat)
kernel_name = 'adaLN_cond__sliding_block_cached__mixer_channel_mlp__decode'

def setup_inputs():

    _w = lambda a: (lambda t: t.to(torch.bfloat16) if t.is_floating_point() else t)(torch.as_tensor(a))

    def _A_setup():
        B, Sq, D = (1, 1, 576)
        Hq, Hkv, Sk, Dh = (32, 16, 32768, 128)
        assert Hq % Hkv == 0, (Hq, Hkv)
        return {'x': _w((lambda *s: torch.randn(*s, dtype=torch.bfloat16) * 0.1)(B, Sq, D)), 'k_cache': _w((lambda *s: torch.randn(*s, dtype=torch.bfloat16) * 0.8)(B, Hkv, Sk, Dh)), 'v_cache': _w((lambda *s: torch.randn(*s, dtype=torch.bfloat16) * 0.8)(B, Hkv, Sk, Dh)), 'wq': _w((lambda *s: torch.randn(*s, dtype=torch.bfloat16) * 0.8)(D, Hq * Dh) * D ** (-0.5)), 'wo': _w((lambda *s: torch.randn(*s, dtype=torch.bfloat16) * 0.8)(Hq * Dh, D) * (Hq * Dh) ** (-0.5))}
    _A_in = _A_setup()

    def _B_setup():
        B, S, D, F = (1, 1, 576, 4608)
        return {'x': _w((lambda *s: torch.randn(*s, dtype=torch.bfloat16) * 0.1)(B, S, D)), 'w1': _w((lambda *s: torch.randn(*s, dtype=torch.bfloat16) * 3.2)(D, F) * D ** (-0.5)), 'b1': _w((lambda *s: torch.randn(*s, dtype=torch.bfloat16) * 3.2)(F)), 'w2': _w((lambda *s: torch.randn(*s, dtype=torch.bfloat16) * 1.6)(F, D) * F ** (-0.5)), 'b2': _w((lambda *s: torch.randn(*s, dtype=torch.bfloat16) * 1.6)(D))}
    _B_in = _B_setup()
    return {'A_x': _A_in['x'], 'A_k_cache': _A_in['k_cache'], 'A_v_cache': _A_in['v_cache'], 'A_wq': _A_in['wq'], 'A_wo': _A_in['wo'], 'B_x': _B_in['x'], 'B_w1': _B_in['w1'], 'B_b1': _B_in['b1'], 'B_w2': _B_in['w2'], 'B_b2': _B_in['b2'], 'c': _w((lambda *s: torch.randn(*s, dtype=torch.bfloat16) * 0.4)(1, 576) * 8.0), 'w_mod': _w((lambda *s: torch.randn(*s, dtype=torch.bfloat16) * 0.4)(576, 6 * 576) * 576 ** (-0.5) * 8.0)}

def reference(A_x, A_k_cache, A_v_cache, A_wq, A_wo, B_x, B_w1, B_b1, B_w2, B_b2, c, w_mod):

    def _A_ref(x, k_cache, v_cache, wq, wo):
        B, Sq, D = x.shape
        Hq, Dh = (32, 128)
        Hkv, Sk = (k_cache.shape[1], k_cache.shape[2])
        W = min(4096, max(256, Sk // 4))
        rep = Hq // Hkv
        q = (lambda x, *d: x.permute(*d))((x @ wq).reshape(B, Sq, Hq, Dh), 0, 2, 1, 3)
        k = (lambda x, n, axis: torch.repeat_interleave(x, n, dim=axis))(k_cache[:, :, Sk - W:, :], rep, axis=1)
        v = (lambda x, n, axis: torch.repeat_interleave(x, n, dim=axis))(v_cache[:, :, Sk - W:, :], rep, axis=1)
        scores = torch.einsum('bhqd,bhkd->bhqk', q, k) * Dh ** (-0.5)
        p = _softmax(scores, axis=-1)
        o = torch.einsum('bhqk,bhkd->bhqd', p, v)
        return (lambda x, *d: x.permute(*d))(o, 0, 2, 1, 3).reshape(B, Sq, Hq * Dh) @ wo

    def _B_ref(x, w1, b1, w2, b2):
        y = _layernorm(x, axis=-1)
        h = _gelu(torch.einsum('bsd,df->bsf', y, w1) + b1)
        return torch.einsum('bsf,fd->bsd', h, w2) + b2
    x = A_x
    mod = (_silu(c) @ w_mod).reshape(c.shape[0], 6, 1, -1)
    sa, ca, ga, sb, cb, gb = (mod[:, 0].clone(), mod[:, 1].clone(), mod[:, 2].clone(), mod[:, 3].clone(), mod[:, 4].clone(), mod[:, 5].clone())
    h = _layernorm(x, axis=-1) * (1 + ca) + sa
    x = x + ga * _A_ref(h, A_k_cache, A_v_cache, A_wq, A_wo)
    h = _layernorm(x, axis=-1) * (1 + cb) + sb
    x = x + gb * _B_ref(h, B_w1, B_b1, B_w2, B_b2)
    return x
```

```cpp
#include <cuda_runtime.h>
#include <cuda_bf16.h>
#include <cuda.h>
#include <stdint.h>

#define RATE_A 3.05
#define RATE_B 3.05
#define RATE_W1 2.9
#define TOFF 600
#define BDELAY 700
#define FDELAY 250
#define XDELAY 0
#define ADELAY -1
#define CAPN 6

namespace {

constexpr int SK = 32768, WIN = 4096, FF = 4608;
constexpr int NCTA = 128;
constexpr int NCONS = 576;
constexpr int NTHREADS = NCONS + 64;

constexpr int OFF_K = 0;
constexpr int OFF_M = 131072;
constexpr int OFF_WQ = OFF_M + 31744;
constexpr int OFF_VA = 199680;
constexpr int OFF_VB = 134144;
constexpr int OFF_VC = 0;
constexpr int OFF_WO = 49152;
constexpr int OFF_W1 = OFF_WO + 36864;
constexpr int OFF_W2 = OFF_VB;
constexpr int OFF_MISC = OFF_VA + 16384;
constexpr int OFF_BAR = OFF_MISC;
constexpr int OFF_S = OFF_BAR + 448;
constexpr int OFF_H = OFF_S + 128;
constexpr int OFF_O = OFF_H + 192;
constexpr int OFF_HH = OFF_O + 128;
constexpr int OFF_Q = OFF_HH + 128;
constexpr int OFF_P = OFF_Q + 512;
constexpr int OFF_XN = OFF_P + 2048;
constexpr int OFF_ST = OFF_XN + 2304;
constexpr int OFF_WMX = OFF_ST + 4608;
constexpr int OFF_WSM = OFF_WMX + 128;
constexpr int OFF_OWN = OFF_P;
constexpr int OFF_COEF = OFF_WSM + 128;
constexpr int SMEM_BYTES = OFF_COEF + 32;
constexpr int OFF_FB = OFF_VC;
constexpr int OFF_RED = OFF_VC + 8192;
static_assert(SMEM_BYTES <= 232448, "smem");
static_assert(OFF_W1 + 46080 <= OFF_VB, "w1");

enum { G_M = 0, G_WQ = 3, G_K = 6, G_V = 22, G_WO = 38, G_W1 = 39, G_W2 = 45, NFULL = 48, E_B = NFULL, E_S, E_V, R_HH, NBAR };
static_assert(NBAR <= 56, "bars");

constexpr int dt_ns(int bytes, double rate) { return (int)(bytes * 128.0 / (rate * 1000.0) + 0.5); }
constexpr int DT_WQ = dt_ns(12288, RATE_A), DT_KV = dt_ns(8192, RATE_A), DT_WO = dt_ns(9216, RATE_B), DT_W1 = dt_ns(6912, RATE_W1);
constexpr int T_M2 = TOFF, T_WQ = T_M2 + dt_ns(10368, RATE_A), T_KV = T_WQ + 3 * DT_WQ, T_WO = T_KV + 32 * DT_KV;
constexpr int T_W1 = T_WO + 4 * DT_WO, T_W2 = T_W1 + 6 * DT_W1;
static_assert(CAPN <= 6 && CAPN >= 4, "cap dependency must name an existing, earlier granule");

__device__ unsigned g_epoch;
__device__ __align__(128) float g_partM[8 * 16 * 432];
__device__ __align__(128) float g_modF[4 * 576];
__device__ __align__(128) float g_partQ[16 * 8 * 256];
__device__ __align__(128) float g_partS[16 * 8 * 8];
__device__ __align__(128) float g_partA[128 * 8 * 32];
__device__ __align__(128) float g_part2[2][18 * 128 * 32];
__device__ __align__(128) float g_x1[576];

#define TL(i) do { } while (0)

struct Params { CUtensorMap m[8]; };

constexpr unsigned SPIN_LIMIT = 1u << 22;

__device__ __forceinline__ void mbar_init(uint32_t bar, int cnt) {
    asm volatile("mbarrier.init.shared::cta.b64 [%0], %1;" ::"r"(bar), "r"(cnt) : "memory");
}
__device__ __forceinline__ void mbar_expect(uint32_t bar, uint32_t bytes) {
    asm volatile("mbarrier.arrive.expect_tx.shared::cta.b64 _, [%0], %1;" ::"r"(bar), "r"(bytes) : "memory");
}
__device__ __forceinline__ void mbar_arrive(uint32_t bar) {
    asm volatile("mbarrier.arrive.shared::cta.b64 _, [%0];" ::"r"(bar) : "memory");
}
__device__ __forceinline__ void mbar_wait(uint32_t bar) {
    asm volatile("{\n.reg .pred p;\n.reg .u32 n;\nmov.u32 n, 0;\n"
                 "W_%=:\nmbarrier.try_wait.parity.shared::cta.b64 p, [%0], 0;\n@p bra D_%=;\n"
                 "add.u32 n, n, 1;\nsetp.lt.u32 p, n, 4000000;\n@p bra W_%=;\ntrap;\nD_%=:\n}"
                 ::"r"(bar) : "memory");
}
__device__ __forceinline__ bool mbar_test(uint32_t bar) {
    uint32_t ok;
    asm volatile("{\n.reg .pred p;\nmbarrier.test_wait.parity.shared::cta.b64 p, [%1], 0;\nselp.u32 %0, 1, 0, p;\n}" : "=r"(ok) : "r"(bar) : "memory");
    return __all_sync(~0u, ok);
}
__device__ __forceinline__ void tma3(uint32_t dst, const CUtensorMap* m, int c0, int c1, int c2, uint32_t bar, uint64_t pol) {
    asm volatile("cp.async.bulk.tensor.3d.shared::cluster.global.mbarrier::complete_tx::bytes.L2::cache_hint "
                 "[%0], [%1, {%3, %4, %5}], [%2], %6;"
                 ::"r"(dst), "l"(m), "r"(bar), "r"(c0), "r"(c1), "r"(c2), "l"(pol) : "memory");
}
__device__ __forceinline__ uint32_t gtime() { uint32_t t; asm volatile("mov.u32 %0, %globaltimer_lo;" : "=r"(t)); return t; }
__device__ __forceinline__ bool elect() {
    uint32_t p; asm volatile("{\n.reg .pred p;\nelect.sync _|p, 0xffffffff;\nselp.u32 %0, 1, 0, p;\n}" : "=r"(p)); return p;
}
__device__ __forceinline__ void bar_sync(int id, int n) { asm volatile("bar.sync %0, %1;" ::"r"(id), "r"(n) : "memory"); }
__device__ __forceinline__ void bar_arrive(int id, int n) { asm volatile("bar.arrive %0, %1;" ::"r"(id), "r"(n) : "memory"); }

__device__ __forceinline__ void ldsm4(uint32_t (&r)[4], uint32_t a) {
    asm volatile("ldmatrix.sync.aligned.m8n8.x4.shared.b16 {%0,%1,%2,%3}, [%4];"
                 : "=r"(r[0]), "=r"(r[1]), "=r"(r[2]), "=r"(r[3]) : "r"(a) : "memory");
}
__device__ __forceinline__ void ldsm4t(uint32_t (&r)[4], uint32_t a) {
    asm volatile("ldmatrix.sync.aligned.m8n8.x4.trans.shared.b16 {%0,%1,%2,%3}, [%4];"
                 : "=r"(r[0]), "=r"(r[1]), "=r"(r[2]), "=r"(r[3]) : "r"(a) : "memory");
}
__device__ __forceinline__ void ldsm2t(uint32_t& r0, uint32_t& r1, uint32_t a) {
    asm volatile("ldmatrix.sync.aligned.m8n8.x2.trans.shared.b16 {%0,%1}, [%2];"
                 : "=r"(r0), "=r"(r1) : "r"(a) : "memory");
}
__device__ __forceinline__ void mma16(float (&c)[4], const uint32_t (&a)[4], uint32_t b0, uint32_t b1) {
    asm volatile("mma.sync.aligned.m16n8k16.row.col.f32.bf16.bf16.f32 {%0,%1,%2,%3}, {%4,%5,%6,%7}, {%8,%9}, {%0,%1,%2,%3};"
                 : "+f"(c[0]), "+f"(c[1]), "+f"(c[2]), "+f"(c[3])
                 : "r"(a[0]), "r"(a[1]), "r"(a[2]), "r"(a[3]), "r"(b0), "r"(b1));
}
__device__ __forceinline__ void mma8(float (&c)[4], uint32_t a0, uint32_t a1, uint32_t b0) {
    asm volatile("mma.sync.aligned.m16n8k8.row.col.f32.bf16.bf16.f32 {%0,%1,%2,%3}, {%4,%5}, {%6}, {%0,%1,%2,%3};"
                 : "+f"(c[0]), "+f"(c[1]), "+f"(c[2]), "+f"(c[3]) : "r"(a0), "r"(a1), "r"(b0));
}
__device__ __forceinline__ uint32_t lds32(uint32_t a) {
    uint32_t v; asm volatile("ld.shared.b32 %0, [%1];" : "=r"(v) : "r"(a) : "memory"); return v;
}
__device__ __forceinline__ float ldsf(uint32_t a) {
    float v; asm volatile("ld.shared.f32 %0, [%1];" : "=f"(v) : "r"(a) : "memory"); return v;
}
__device__ __forceinline__ void ldsf2(float& x, float& y, uint32_t a) {
    asm volatile("ld.shared.v2.f32 {%0,%1}, [%2];" : "=f"(x), "=f"(y) : "r"(a) : "memory");
}
__device__ __forceinline__ void ldsf4(float (&r)[4], uint32_t a) {
    asm volatile("ld.shared.v4.f32 {%0,%1,%2,%3}, [%4];" : "=f"(r[0]), "=f"(r[1]), "=f"(r[2]), "=f"(r[3]) : "r"(a) : "memory");
}
__device__ __forceinline__ void lds128(uint32_t (&r)[4], uint32_t a) {
    asm volatile("ld.shared.v4.b32 {%0,%1,%2,%3}, [%4];" : "=r"(r[0]), "=r"(r[1]), "=r"(r[2]), "=r"(r[3]) : "r"(a) : "memory");
}
__device__ __forceinline__ void stsf(uint32_t a, float v) { asm volatile("st.shared.f32 [%0], %1;" ::"r"(a), "f"(v) : "memory"); }
__device__ __forceinline__ void stsf2(uint32_t a, float x, float y) { asm volatile("st.shared.v2.f32 [%0], {%1,%2};" ::"r"(a), "f"(x), "f"(y) : "memory"); }
__device__ __forceinline__ void sts16(uint32_t a, uint32_t v) { asm volatile("st.shared.b16 [%0], %1;" ::"r"(a), "h"((unsigned short)v) : "memory"); }
__device__ __forceinline__ void sts32(uint32_t a, uint32_t v) { asm volatile("st.shared.b32 [%0], %1;" ::"r"(a), "r"(v) : "memory"); }
__device__ __forceinline__ uint32_t pack2(float lo, float hi) {
    uint32_t d; asm("cvt.rn.bf16x2.f32 %0, %1, %2;" : "=r"(d) : "f"(hi), "f"(lo)); return d;
}
__device__ __forceinline__ float bfr(float x) { return __uint_as_float(pack2(0.f, x)); }
__device__ __forceinline__ float fsqrt(float x) { float r; asm("sqrt.approx.ftz.f32 %0, %1;" : "=f"(r) : "f"(x)); return r; }
__device__ __forceinline__ float frcp(float x) { float r; asm("rcp.approx.ftz.f32 %0, %1;" : "=f"(r) : "f"(x)); return r; }
__device__ __forceinline__ float fexp(float x) { float r; asm("ex2.approx.ftz.f32 %0, %1;" : "=f"(r) : "f"(x * 1.4426950408889634f)); return r; }
__device__ __forceinline__ float ln_rden(float var) { return frcp(bfr(fsqrt(bfr(bfr(fmaxf(var, 0.f)) + 1e-5f)))); }
__device__ __forceinline__ int fpos(int k) { return (k & ~31) | ((k & 6) << 2) | ((k >> 2) & 6) | (k & 1); }
__device__ __forceinline__ void stsv(uint32_t base, int k, float v) {
    asm volatile("st.shared.b16 [%0], %1;" ::"r"(base + fpos(k) * 2), "h"((unsigned short)pack2(v, 0.f)) : "memory");
}
__device__ __forceinline__ float ldbf(const __nv_bfloat16* p) {
    return __uint_as_float((uint32_t)__ldg(reinterpret_cast<const unsigned short*>(p)) << 16);
}
__device__ __forceinline__ float sel4(const float (&c)[4], int t) { return (t & 2) ? ((t & 1) ? c[3] : c[2]) : ((t & 1) ? c[1] : c[0]); }
__device__ __forceinline__ float sel22(const float (&c0)[4], const float (&c1)[4], int t) {
    return (t & 2) ? ((t & 1) ? c1[2] : c1[0]) : ((t & 1) ? c0[2] : c0[0]);
}

__device__ __forceinline__ float untag(uint32_t u) { return __uint_as_float(u & ~3u); }
__device__ __forceinline__ void clr(float* p) { asm volatile("st.relaxed.gpu.global.b32 [%0], %1;" ::"l"(p), "r"(0) : "memory"); }
__device__ __forceinline__ void pub(float* p, float a, uint32_t tag) {
    asm volatile("{\n.reg .b32 o;\natom.relaxed.gpu.global.exch.b32 o, [%0], %1;\n}"
                 ::"l"(p), "r"((__float_as_uint(a) & ~3u) | tag) : "memory");
}
__device__ __forceinline__ void pubst(float* p, float a, uint32_t tag) {
    asm volatile("st.relaxed.gpu.global.b32 [%0], %1;" ::"l"(p), "r"((__float_as_uint(a) & ~3u) | tag) : "memory");
}
#define PUB_A pub
#define PUB_O pub
#define PUB_X pub
#define PUB_F pubst
template <int OFF>
__device__ __forceinline__ void ldp(uint32_t& u, const float* p, uint32_t tag) {
    asm volatile("{\n.reg .pred p;\n.reg .b32 t;\nlop3.b32 t, %0, %2, 3, 0x28;\nsetp.ne.u32 p, t, 0;\n"
                 "@p ld.relaxed.gpu.global.b32 %0, [%1+%3];\n}" : "+r"(u) : "l"(p), "r"(tag), "n"(OFF) : "memory");
}
template <int N, int STRIDE, int I = 0>
__device__ __forceinline__ void ldp_all(uint32_t (&u)[N], const float* p, uint32_t tag) {
    if constexpr (I < N) { ldp<I * STRIDE * 4>(u[I], p, tag); ldp_all<N, STRIDE, I + 1>(u, p, tag); }
}
template <int N, int STRIDE>
__device__ __forceinline__ void poll(const float* p, uint32_t tag, float (&v)[N]) {
    uint32_t u[N];
#pragma unroll
    for (int i = 0; i < N; i++) u[i] = 0;
    unsigned it = 0;
#pragma unroll 1
    while (true) {
        ldp_all<N, STRIDE>(u, p, tag);
        uint32_t bad = 0;
#pragma unroll
        for (int i = 0; i < N; i++) asm("lop3.b32 %0, %0, %1, %2, 0xf6;" : "+r"(bad) : "r"(u[i]), "r"(tag));
        if (!(bad & 3)) break;
        if (++it > SPIN_LIMIT) __trap();
    }
#pragma unroll
    for (int i = 0; i < N; i++) v[i] = untag(u[i]);
}
template <int OFF>
__device__ __forceinline__ void ldp4(uint32_t (&u)[4], uint32_t bad, const float* p) {
    asm volatile("{\n.reg .pred p;\n.reg .b32 t;\nand.b32 t, %5, 3;\nsetp.ne.u32 p, t, 0;\n"
                 "@p ld.relaxed.gpu.global.v4.b32 {%0,%1,%2,%3}, [%4+%6];\n}"
                 : "+r"(u[0]), "+r"(u[1]), "+r"(u[2]), "+r"(u[3]) : "l"(p), "r"(bad), "n"(OFF) : "memory");
}
template <int N>
__device__ __forceinline__ float tree_sum(float (&v)[N]) {
#pragma unroll
    for (int s = 1; s < N; s *= 2)
#pragma unroll
        for (int i = 0; i + s < N; i += 2 * s) v[i] += v[i + s];
    return v[0];
}
__device__ __forceinline__ float xadd(float keep, float send, int o) { return keep + __shfl_xor_sync(~0u, send, o); }

__device__ __forceinline__ void sum6_warp(const float (&v)[6], uint32_t st, int warp, int lane) {
    const bool b4 = lane & 16, b3 = lane & 8, b2 = lane & 4;
    const float w0 = xadd(b4 ? v[3] : v[0], b4 ? v[0] : v[3], 16);
    const float w1 = xadd(b4 ? v[4] : v[1], b4 ? v[1] : v[4], 16);
    const float w2 = xadd(b4 ? v[5] : v[2], b4 ? v[2] : v[5], 16);
    const float z0 = xadd(b3 ? w1 : w0, b3 ? w0 : w1, 8);
    const float z1 = xadd(w2, w2, 8);
    float t = xadd(b2 ? z1 : z0, b2 ? z0 : z1, 4);
    t = xadd(t, t, 2);
    t = xadd(t, t, 1);
    if (!(lane & 3)) stsf(st + (lane >> 2) * 192 + warp * 4, t);
}
__device__ __forceinline__ void sum6_total(float (&v)[6], uint32_t st, int lane) {
    const uint32_t row = st + (lane >> 2) * 192;
    float q[4];
    ldsf4(q, row + (lane & 3) * 16);
    const float e = ldsf(row + 64 + (lane & 1) * 4);
    float t = (q[0] + q[1]) + (q[2] + q[3]) + ((lane & 2) ? 0.f : e);
    t = xadd(t, t, 1);
    t = xadd(t, t, 2);
    v[0] = __shfl_sync(~0u, t, 0);  v[1] = __shfl_sync(~0u, t, 8);  v[2] = __shfl_sync(~0u, t, 4);
    v[3] = __shfl_sync(~0u, t, 16); v[4] = __shfl_sync(~0u, t, 24); v[5] = __shfl_sync(~0u, t, 20);
}

template <int DELAY>
__device__ __forceinline__ float owner_sum(const float* part, uint32_t own, uint32_t tag, int warp, int lane) {
    const float* p = part + warp * 256 + lane * 4;
    if (DELAY) { const uint32_t t = gtime(); while ((int)(gtime() - t) < DELAY) {} }
    uint32_t u[4] = {0, 0, 0, 0}, w[4] = {0, 0, 0, 0}, bu = 1, bw = 1;
    unsigned it = 0;
#pragma unroll 1
    while (true) {
        ldp4<0>(u, bu, p);
        ldp4<512>(w, bw, p);
        bu = (u[0] ^ tag) | (u[1] ^ tag) | (u[2] ^ tag) | (u[3] ^ tag);
        bw = (w[0] ^ tag) | (w[1] ^ tag) | (w[2] ^ tag) | (w[3] ^ tag);
        if (!((bu | bw) & 3)) break;
        if (++it > SPIN_LIMIT) __trap();
    }
    float s[4];
#pragma unroll
    for (int i = 0; i < 4; i++) s[i] = untag(u[i]) + untag(w[i]);
    const bool hi = lane & 16, h8 = lane & 8;
    const float k0 = xadd(hi ? s[2] : s[0], hi ? s[0] : s[2], 16);
    const float k1 = xadd(hi ? s[3] : s[1], hi ? s[1] : s[3], 16);
    const float k = xadd(h8 ? k1 : k0, h8 ? k0 : k1, 8);
    stsf(own + (((lane & 7) * 4 + (lane >> 4) * 2 + ((lane >> 3) & 1)) * 20 + warp) * 4, k);
    if (warp != 0) { bar_arrive(8, 512); return 0.f; }
    bar_sync(8, 512);
    float q[4][4];
#pragma unroll
    for (int i = 0; i < 4; i++) ldsf4(q[i], own + lane * 80 + i * 16);
#pragma unroll
    for (int i = 0; i < 4; i++) s[i] = (q[i][0] + q[i][1]) + (q[i][2] + q[i][3]);
    return (s[0] + s[1]) + (s[2] + s[3]);
}

__global__ void __launch_bounds__(NTHREADS, 1)
fused_block_kernel(const __grid_constant__ Params prm,
                   const __nv_bfloat16* __restrict__ x_in, const __nv_bfloat16* __restrict__ c_in,
                   const __nv_bfloat16* __restrict__ b1, const __nv_bfloat16* __restrict__ b2,
                   __nv_bfloat16* __restrict__ out) {
    extern __shared__ __align__(1024) unsigned char smem[];
    const uint32_t sb = (uint32_t)__cvta_generic_to_shared(smem);
    const int tid = threadIdx.x, warp = __shfl_sync(~0u, tid >> 5, 0), lane = tid & 31;
    const int cta = blockIdx.x, g = cta >> 3, r = cta & 7;
    const uint32_t bars = sb + OFF_BAR;
#define BAR(i) (bars + (i) * 8)

    if (warp == 18) {
        uint64_t pf;
        asm volatile("createpolicy.fractional.L2::evict_first.b64 %0, 1.0;" : "=l"(pf));
        const uint32_t t0 = gtime() - 160 + cta * 5 / 2;
        const bool el = elect();
#define TLG() do { } while (0)
#define LOAD(n, dst, map, c0, c1, c2) do { if (el) tma3(sb + (dst), &prm.m[map], c0, c1, c2, BAR(n), pf); TLG(); } while (0)
#define EXPECT(n, bytes) do { if (el) mbar_expect(BAR(n), bytes); } while (0)
#define AT(t) do { } while ((int)(gtime() - t0) < (int)(t))
        if (el) {
            mbar_init(BAR(0), 1);
            mbar_init(BAR(1), 1);
            asm volatile("fence.proxy.async.shared::cta;" ::: "memory");
        }
        EXPECT(G_M, 10368);     LOAD(G_M, OFF_M, 0, 72 * r, 36 * g, 0);
        EXPECT(G_M + 1, 10368); LOAD(G_M + 1, OFF_M + 10368, 0, 72 * r, 36 * g, 2);
        if (el) {
            asm volatile("prefetch.tensormap [%0];" ::"l"(&prm.m[1]) : "memory");
            asm volatile("prefetch.tensormap [%0];" ::"l"(&prm.m[2]) : "memory");
#pragma unroll
            for (int i = 2; i < NFULL; i++) mbar_init(BAR(i), 1);
            mbar_init(BAR(E_B), 18);
            mbar_init(BAR(E_S), 16);
            mbar_init(BAR(E_V), 8);
            mbar_init(BAR(R_HH), 3);
            asm volatile("fence.mbarrier_init.release.cluster;" ::: "memory");
            asm volatile("fence.proxy.async.shared::cta;" ::: "memory");
        }
        __syncwarp();
        bar_arrive(5, NTHREADS);
        EXPECT(G_M + 2, 10368);
        AT(T_M2);
        LOAD(G_M + 2, OFF_M + 2 * 10368, 0, 72 * r, 36 * g, 4);
#pragma unroll 1
        for (int i = 0; i < 3; i++) {
            EXPECT(G_WQ + i, 12288);
            AT(T_WQ + i * DT_WQ);
            LOAD(G_WQ + i, OFF_WQ + i * 12288, 1, 0, 72 * r + 24 * i, 4 * g);
        }
        if (el) {
#pragma unroll
            for (int i = 3; i < 8; i++) asm volatile("prefetch.tensormap [%0];" ::"l"(&prm.m[i]) : "memory");
        }
        EXPECT(G_WO, 36864);
        EXPECT(G_W2, 18432);
        EXPECT(G_W2 + 1, 18432);
        EXPECT(G_W2 + 2, 4608);
        const int krow = g * SK + (SK - WIN) + 32 * r;
#pragma unroll 1
        for (int i = 0; i < 32; i++) {
            EXPECT(G_K + i, 8192);
            if (i == 18) mbar_wait(BAR(E_B));
            if (i == 26) mbar_wait(BAR(E_S));
            mbar_wait(BAR(G_K + i - CAPN));
            const int dst = i * 8192 + (i < 16 ? OFF_K : (i < 18 ? OFF_VA - 16 * 8192 : (i < 26 ? OFF_VB - 18 * 8192 : OFF_VC - 26 * 8192)));
            AT(T_KV + i * DT_KV);
            LOAD(G_K + i, dst, 2 + (i >> 4), 0, krow + 256 * ((i + g) & 15), 0);
        }
#pragma unroll 1
        for (int i = 0; i < 4; i++) {
            mbar_wait(BAR(G_WO + i - CAPN));
            AT(T_WO + i * DT_WO);
            LOAD(G_WO, OFF_WO + i * 9216, 4, 0, 256 * g + 16 * r + (i >> 1) * 128 + (i & 1) * 8, 0);
        }
#pragma unroll 1
        for (int i = 0; i < 6; i++) {
            EXPECT(G_W1 + i, 7680);
            AT(T_W1 + i * DT_W1);
            LOAD(G_W1 + i, OFF_W1 + i * 7680, 5, (36 * cta) & ~7, 96 * i, 0);
        }
        mbar_wait(BAR(E_V));
#pragma unroll 1
        for (int i = 0; i < 5; i++) {
            AT(T_W2 + i * DT_WO);
            LOAD(G_W2 + (i >> 1), OFF_W2 + i * 9216, 6 + (i >> 2), 0, 36 * cta + 8 * i, 0);
        }
        return;
    }
    unsigned epoch;
    asm volatile("ld.relaxed.gpu.global.u32 %0, [%1];" : "=r"(epoch) : "l"(&g_epoch) : "memory");
    const int gq = lane >> 2, t4 = lane & 3;

    if (warp == 19) {
        if (lane < 8) clr(g_partS + cta * 8 + lane);
        const int e = 24 * g + lane;
        float* const mdst = g_modF + (e / 72) * 576 + 72 * r + e % 72;
        if (g < 12 && lane < 24) clr(mdst);
        const uint32_t tag = 1 + (epoch & 1);
        bar_sync(5, NTHREADS);
        mbar_wait(BAR(G_M + 2));
        if (g < 12 && lane < 24) {
            float v[16];
            poll<16, 432>(g_partM + r * 16 * 432 + 144 + e, tag, v);
            pub(mdst, bfr(tree_sum(v)), tag);
        }
        __syncwarp();
        bar_sync(3, 512 + 32);
        float wt[8];
        {
            float m = ldsf(sb + OFF_WMX + lane * 4), l = ldsf(sb + OFF_WSM + lane * 4);
#pragma unroll
            for (int o = 2; o <= 16; o <<= 1) { m = fmaxf(m, __shfl_xor_sync(~0u, m, o)); l += __shfl_xor_sync(~0u, l, o); }
            if (lane < 8) pub(g_partS + cta * 8 + lane, (lane & 2) ? l : m, tag);
            float v[2];
            poll<2, 2>(g_partS + (g * 8 + (lane & 7)) * 8 + (lane >> 4), tag, v);
            float mg = v[0];
#pragma unroll
            for (int o = 1; o <= 4; o <<= 1) mg = fmaxf(mg, __shfl_xor_sync(~0u, mg, o));
            const float w = fexp(v[0] - mg);
            float lg = w * v[1];
#pragma unroll
            for (int o = 1; o <= 4; o <<= 1) lg += __shfl_xor_sync(~0u, lg, o);
            const float wn = w * frcp(lg);
#pragma unroll
            for (int i = 0; i < 8; i++) wt[i] = __shfl_sync(~0u, wn, (lane & 16) + i);
        }
        TL(30);
        {
            float v[8];
            if (ADELAY >= 0) { mbar_wait(BAR(G_V + 15)); const uint32_t t = gtime(); while ((int)(gtime() - t) < ADELAY) {} }
            poll<8, 32>(g_partA + cta * 256 + lane, tag, v);
#pragma unroll
            for (int i = 0; i < 8; i++) v[i] *= wt[i];
            stsv(sb + OFF_O, lane, tree_sum(v));
            __syncwarp();
            bar_arrive(4, NCONS + 32);
        }
        TL(31);
        float pre[6], v[6];
        bar_sync(9, NCONS + 32);
        sum6_total(pre, sb + OFF_ST + 1536, lane);
        bar_sync(6, NCONS + 32);
        sum6_total(v, sb + OFF_ST + 3072, lane);
        constexpr float RN = 1.f / 576.f;
        const float mean = v[0] * RN, mb = bfr(mean);
        const float r1 = ln_rden(v[1] * RN - mean * mean);
        const float m2 = (r1 * (v[2] - mb * pre[0]) + pre[3]) * RN;
        const float e2 = (r1 * (r1 * (v[3] - mb * (2.f * v[4] - mb * pre[1])) + 2.f * (v[5] - mb * pre[2])) + pre[4]) * RN;
        const float r2 = ln_rden(e2 - m2 * m2), r12 = r1 * r2;
        if (lane < 2) stsf2(sb + OFF_COEF + lane * 8, lane ? -r12 * mb : r12, lane ? r2 : -r2 * bfr(m2));
        __syncwarp();
        bar_arrive(10, 96 + 32);
        TL(34);
        return;
    }

    float* const pdst = g_part2[0] + (warp * 128 + cta) * 32 + t4 * 8 + gq;
    const bool owner = cta < 18 && warp < 16;
    const int col = 32 * cta + lane;
    if (tid < 432) clr(g_partM + (r * 16 + g) * 432 + tid);
    if (tid < 256) { clr(g_partQ + cta * 256 + tid); clr(g_partA + ((g * 8 + warp) * 8 + r) * 32 + lane); }
    clr(pdst);
    clr(pdst + 18 * 128 * 32);
    float xc = 0.f, b2c = 0.f, b1v = 0.f;
    const int unit = (tid >> 1) - (cta & 1) * 4;
    if (unit >= 0 && unit < 36) b1v = ldbf(b1 + 36 * cta + unit);
    if (owner && warp == 0) { xc = ldbf(x_in + col); b2c = ldbf(b2 + col); clr(g_x1 + col); }
    {
        const float xv = ldbf(x_in + tid);
        if (tid < 40) {
            float sv = 0.f;
            if (tid < 36) {
                const float cv = ldbf(c_in + 36 * g + tid);
                sv = cv * frcp(1.f + fexp(-cv));
            }
            stsv(sb + OFF_S, tid, sv);
            stsv(sb + OFF_HH, tid, 0.f);
        }
        float v[6] = {xv, xv * xv, 0.f, 0.f, 0.f, 0.f};
        sum6_warp(v, sb + OFF_ST, warp, lane);
        bar_sync(1, NCONS);
        sum6_total(v, sb + OFF_ST, lane);
        const float mean = v[0] * (1.f / 576.f);
        stsf(sb + OFF_XN + tid * 4, bfr(bfr(xv - bfr(mean)) * ln_rden(v[1] * (1.f / 576.f) - mean * mean)));
    }
    const uint32_t tag = 1 + (epoch & 1);
    bar_sync(5, NTHREADS);
    if (warp == 0) TL(8);
    const int mi = lane >> 3, l7 = lane & 7;
    const int krw = l7 + ((lane >> 4) << 3);

    {
        uint32_t b[4];
        lds128(b, sb + OFF_S + t4 * 16);
        const uint32_t bt = lds32(sb + OFF_S + 64 + t4 * 16);
        const int tl = warp < 9 ? warp : warp - 9, cg = 2 * tl + (mi & 1);
        const uint32_t ca = sb + OFF_M + (cg >= 9 ? 5184 - 144 : 0) + cg * 16;
#pragma unroll 1
        for (int u = warp >= 9; u < (warp < 9 ? 1 : 3); u++) {
            mbar_wait(BAR(G_M + u));
            uint32_t a0[4], a1[4], a2, a3;
            ldsm4t(a0, ca + u * 10368 + krw * 144);
            ldsm4t(a1, ca + u * 10368 + krw * 144 + 16 * 144);
            ldsm2t(a2, a3, ca + u * 10368 + min(32 + l7, 35) * 144);
            float c[4] = {0.f, 0.f, 0.f, 0.f};
            mma16(c, a0, b[0], b[1]);
            mma16(c, a1, b[2], b[3]);
            mma8(c, a2, a3, bt);
            if (t4 < 2) pub(g_partM + (r * 16 + g) * 432 + u * 144 + tl * 16 + t4 * 8 + gq, t4 ? c[2] : c[0], tag);
        }
        if (warp == 0) TL(10);
    }

    if (warp >= 16) {
        __syncwarp();
        if (lane == 0) mbar_arrive(BAR(E_B));
    } else {
        if (tid < 160) {
            float s = 0.f;
            if (tid < 144) {
                float v[16];
                poll<16, 432>(g_partM + r * 16 * 432 + (tid & 1) * 72 + (tid >> 1), tag, v);
                s = bfr(tree_sum(v));
            }
            const float ca = __shfl_xor_sync(~0u, s, 1);
            if (tid < 144 && !(tid & 1))
                stsv(sb + OFF_H, tid >> 1, bfr(ldsf(sb + OFF_XN + (72 * r + (tid >> 1)) * 4) * bfr(1.f + ca)) + s);
        }
        {
            uint32_t a[4][4], a4, a5;
            const uint32_t base = sb + OFF_WQ + (warp >> 2) * 3072 + l7 * 128 + (((2 * (warp & 3) + (mi & 1)) ^ l7) << 4);
            const bool up = lane & 16;
            mbar_wait(BAR(G_WQ));
            ldsm4t(a[0], base + (up ? 1024 : 0));
            mbar_wait(BAR(G_WQ + 1));
            ldsm4t(a[1], base + (up ? 12288 : 2048));
            ldsm4t(a[2], base + (up ? 12288 + 2048 : 12288 + 1024));
            mbar_wait(BAR(G_WQ + 2));
            ldsm4t(a[3], base + (up ? 24576 + 1024 : 24576));
            ldsm2t(a4, a5, base + 24576 + 2048);
            bar_sync(2, 512);
            if (warp == 0) TL(11);
            uint32_t b0[4], b1r[4];
            lds128(b0, sb + OFF_H + t4 * 16);
            lds128(b1r, sb + OFF_H + 64 + t4 * 16);
            const uint32_t bt = lds32(sb + OFF_H + 128 + t4 * 16);
            float c0[4] = {0.f, 0.f, 0.f, 0.f}, c1[4] = {0.f, 0.f, 0.f, 0.f};
            mma16(c0, a[0], b0[0], b0[1]);
            mma16(c1, a[1], b0[2], b0[3]);
            mma16(c0, a[2], b1r[0], b1r[1]);
            mma16(c1, a[3], b1r[2], b1r[3]);
            mma8(c0, a4, a5, bt);
            if (t4 < 2) pub(g_partQ + cta * 256 + warp * 16 + t4 * 8 + gq, t4 ? c0[2] + c1[2] : c0[0] + c1[0], tag);
            if (lane == 0) mbar_arrive(BAR(E_B));
        }
        if (warp == 0) TL(12);
        if (tid < 256) {
            float v[8];
            poll<8, 256>(g_partQ + g * 8 * 256 + tid, tag, v);
            stsv(sb + OFF_Q, tid, tree_sum(v));
        }
        bar_sync(2, 512);
        if (warp == 0) TL(13);
        float sc[2];
        {
            uint32_t qb[4][4];
#pragma unroll
            for (int i = 0; i < 4; i++) lds128(qb[i], sb + OFF_Q + (gq & 1) * 256 + i * 64 + t4 * 16);
            mbar_wait(BAR(G_K + warp));
#pragma unroll
            for (int u = 0; u < 2; u++) {
                const uint32_t base = sb + OFF_K + warp * 8192 + (u * 16 + (lane & 15)) * 128;
                float c0[4] = {0.f, 0.f, 0.f, 0.f}, c1[4] = {0.f, 0.f, 0.f, 0.f};
#pragma unroll
                for (int ks = 0; ks < 4; ks++) {
                    const int sw = ((2 * ks + (lane >> 4)) ^ l7) << 4;
                    uint32_t a[4], a2[4];
                    ldsm4(a, base + sw);
                    ldsm4(a2, base + 4096 + sw);
                    mma16(c0, a, qb[ks >> 1][2 * (ks & 1)], qb[ks >> 1][2 * (ks & 1) + 1]);
                    mma16(c1, a2, qb[2 + (ks >> 1)][2 * (ks & 1)], qb[2 + (ks >> 1)][2 * (ks & 1) + 1]);
                }
                sc[u] = bfr(bfr(sel4(c0, t4) + sel4(c1, t4)) * 0.08838834764831845f);
            }
            if (lane == 0) mbar_arrive(BAR(E_S));
            float mx = fmaxf(sc[0], sc[1]);
#pragma unroll
            for (int o = 2; o <= 16; o <<= 1) mx = fmaxf(mx, __shfl_xor_sync(~0u, mx, o));
            if (lane < 2) stsf(sb + OFF_WMX + (warp * 2 + lane) * 4, mx);
        }
        bar_sync(2, 512);
        if (warp == 0) TL(14);
        {
            float m = ldsf(sb + OFF_WMX + lane * 4);
#pragma unroll
            for (int o = 2; o <= 16; o <<= 1) m = fmaxf(m, __shfl_xor_sync(~0u, m, o));
            const float p0 = fexp(sc[0] - m), p1 = fexp(sc[1] - m);
            const int key = warp * 32 + gq + ((t4 & 2) << 2);
            stsv(sb + OFF_P + (t4 & 1) * 1024, key, p0);
            stsv(sb + OFF_P + (t4 & 1) * 1024, key + 16, p1);
            float l = p0 + p1;
#pragma unroll
            for (int o = 2; o <= 16; o <<= 1) l += __shfl_xor_sync(~0u, l, o);
            if (lane < 2) stsf(sb + OFF_WSM + (warp * 2 + lane) * 4, l);
        }
        bar_sync(3, 512 + 32);
        if (warp == 0) TL(15);
    }
    float sv, cv, gg[2] = {0.f, 0.f};
    {
        float v[2];
        poll<2, 576>(g_modF + 576 + tid, tag, v);
        if (owner && warp == 0) poll<2, 3 * 576>(g_modF + col, tag, gg);
        sv = v[0]; cv = bfr(1.f + v[1]);
        const float pre[6] = {cv, cv * cv, cv * sv, sv, sv * sv, 0.f};
        sum6_warp(pre, sb + OFF_ST + 1536, warp, lane);
        __syncwarp();
        bar_arrive(9, NCONS + 32);
    }
    if (warp < 8) {
        float c0[4] = {0.f, 0.f, 0.f, 0.f}, c1[4] = {0.f, 0.f, 0.f, 0.f};
        const uint32_t voff = sb + (warp >> 2) * 4096 + krw * 128 + (((2 * (warp & 3) + (mi & 1)) ^ l7) << 4);
        const uint32_t pa = sb + OFF_P + (gq & 1) * 1024 + t4 * 16;
#pragma unroll 1
        for (int ck = 0; ck < 16; ck++) {
            const uint32_t src = voff + ck * 8192 + (ck < 2 ? OFF_VA : (ck < 10 ? OFF_VB - 2 * 8192 : OFF_VC - 10 * 8192));
            uint32_t pb[4], a[4], a2[4];
            lds128(pb, pa + ck * 64);
            mbar_wait(BAR(G_V + ck));
            ldsm4t(a, src);
            ldsm4t(a2, src + 2048);
            mma16(c0, a, pb[0], pb[1]);
            mma16(c1, a2, pb[2], pb[3]);
            if (ck == 7 && lane == 0) mbar_arrive(BAR(E_V));
        }
        PUB_A(g_partA + ((g * 8 + warp) * 8 + r) * 32 + (t4 & 1) * 16 + gq + ((t4 & 2) << 2), sel4(c0, t4) + sel4(c1, t4), tag);
        if (warp == 0) TL(16);
    }
    const uint32_t woff = (lane >> 4) * 9216 + (warp >> 1) * 1024 + l7 * 128 + ((((warp & 1) * 4 + (mi & 1)) ^ l7) << 4);
    {
        uint32_t a[4][4], b[4];
        mbar_wait(BAR(G_WO));
#pragma unroll
        for (int i = 0; i < 4; i++) ldsm4t(a[i], (sb + OFF_WO + (i & 1) * 18432 + woff) ^ ((i & 2) << 4));
        if (warp == 17) TL(18);
        bar_sync(4, NCONS + 32);
        lds128(b, sb + OFF_O + t4 * 16);
        float c0[4] = {0.f, 0.f, 0.f, 0.f}, c1[4] = {0.f, 0.f, 0.f, 0.f};
        mma16(c0, a[0], b[0], b[1]);
        mma16(c1, a[2], b[0], b[1]);
        mma16(c0, a[1], b[2], b[3]);
        mma16(c1, a[3], b[2], b[3]);
        PUB_O(pdst, sel22(c0, c1, t4), tag);
        if (warp == 0) TL(19);
    }
    const uint32_t tpub = gtime();
    const uint32_t fb = sb + OFF_FB + warp * 320 + fpos(lane) * 2;
    sts16(fb + 128, __float_as_uint(cv) >> 16);
    sts16(fb + 192, __float_as_uint(sv) >> 16);
    sts16(fb + 256, 0x3f80);
    float x1c = 0.f;
    if (owner) {
        const float k = owner_sum<BDELAY>(g_part2[0] + cta * 4096, sb + OFF_OWN, tag, warp, lane);
        if (warp == 0) {
            x1c = bfr(xc + bfr(gg[0] * bfr(k)));
            PUB_X(g_x1 + col, x1c, tag);
            TL(32);
        }
    }
    {
        uint32_t w[6][4], b[4];
        const uint32_t w1bar = BAR(G_W1 + warp / 3);
        bool w1rdy = false;
#define LOAD_W1() _Pragma("unroll") for (int i = 0; i < 6; i++) \
            ldsm4t(w[i], sb + OFF_W1 + (warp * 32 + (i & 1) * 16 + krw) * 80 + (i < 4 ? ((i & 2) + (mi & 1)) * 16 : 64))
        uint32_t xu = 0;
        {
            unsigned it = 0;
#pragma unroll 1
            while (true) {
                if ((int)(gtime() - tpub) >= XDELAY) ldp<0>(xu, g_x1 + tid, tag);
                if (!w1rdy && mbar_test(w1bar)) { LOAD_W1(); w1rdy = true; }
                if (__all_sync(~0u, !((xu ^ tag) & 3))) break;
                if (++it > SPIN_LIMIT) __trap();
            }
        }
        if (warp == 17) TL(21);
        const float a = untag(xu), ac = a * cv, hi = bfr(ac);
        sts16(fb, __float_as_uint(hi) >> 16);
        sts16(fb + 64, __float_as_uint(ac - hi) >> 16);
        __syncwarp();
        lds128(b, sb + OFF_FB + warp * 320 + min(gq, 4) * 64 + t4 * 16);
        float c[3][4];
#pragma unroll
        for (int i = 0; i < 3; i++) c[i][0] = c[i][1] = c[i][2] = c[i][3] = 0.f;
#define MMA_W1() do { _Pragma("unroll") for (int i = 0; i < 3; i++) mma16(c[i], w[2 * i], b[0], b[1]); \
                      _Pragma("unroll") for (int i = 0; i < 3; i++) mma16(c[i], w[2 * i + 1], b[2], b[3]); } while (0)
        if (w1rdy) MMA_W1();
        const float v[6] = {a, a * a, ac, ac * ac, ac * cv, ac * sv};
        sum6_warp(v, sb + OFF_ST + 3072, warp, lane);
        __syncwarp();
        bar_arrive(6, NCONS + 32);
        if (!w1rdy) { mbar_wait(w1bar); LOAD_W1(); MMA_W1(); }
        const uint32_t red = sb + OFF_RED + warp * 768 + gq * 16 + t4 * 8;
#pragma unroll
        for (int j = 0; j < 5; j++) {
            const float e0 = c[j >> 1][2 * (j & 1)], e1 = c[j >> 1][2 * (j & 1) + 1];
            const float one = __shfl_down_sync(~0u, e0, 2);
            if (t4 < 2) stsf2(red + j * 128, t4 ? e0 : e0 + e1, t4 ? e1 : one);
        }
        __syncwarp();
        if (warp == 17) TL(22);
        const int trow = (warp >> 1) * 4 + (l7 & 3);
#define LOAD_W2(k) do { ldsm4t(w[k], sb + OFF_W2 + (k) * 18432 + woff); ldsm4t(w[2 + (k)], (sb + OFF_W2 + (k) * 18432 + woff) ^ 32); } while (0)
        if (warp >= 3) {
            bar_arrive(1, NCONS);
        } else {
            bar_sync(1, NCONS);
            if (warp == 0) TL(26);
            float v0[18], v1[18], k0, k1;
#pragma unroll
            for (int i = 0; i < 18; i++) ldsf2(v0[i], v1[i], sb + OFF_RED + i * 768 + tid * 8);
            const float s0 = tree_sum(v0), s1 = tree_sum(v1);
            bar_sync(10, 96 + 32);
            ldsf2(k0, k1, sb + OFF_COEF + (lane & 1) * 8);
            float u = k0 * s0 + k1 * s1;
            u = xadd(u, u, 1);
            u = bfr(bfr(u) + b1v);
            const float z2 = 1.5957691216057308f * (u + 0.044715f * u * u * u);
            u *= frcp(1.f + fexp(-z2));
            if (!(lane & 1) && unit >= 0 && unit < 36) stsv(sb + OFF_HH, unit, u);
            __syncwarp();
            if (lane == 0) mbar_arrive(BAR(R_HH));
            if (warp == 0) TL(27);
        }
        mbar_wait(BAR(G_W2));
        LOAD_W2(0);
        mbar_wait(BAR(G_W2 + 1));
        LOAD_W2(1);
        mbar_wait(BAR(G_W2 + 2));
        ldsm4t(w[4], sb + OFF_W2 + 36864 + trow * 128 + ((((warp & 1) * 4 + mi) ^ (trow & 7)) << 4));
        if (warp == 17) TL(24);
        mbar_wait(BAR(R_HH));
        lds128(b, sb + OFF_HH + t4 * 16);
        const uint32_t bt = lds32(sb + OFF_HH + 64 + t4 * 16);
        float c0[4] = {0.f, 0.f, 0.f, 0.f}, c1[4] = {0.f, 0.f, 0.f, 0.f}, c2[4] = {0.f, 0.f, 0.f, 0.f};
        mma16(c0, w[0], b[0], b[1]);
        mma16(c1, w[2], b[0], b[1]);
        mma16(c2, w[4], (gq & 1) ? 0u : bt, (gq & 1) ? bt : 0u);
        mma16(c0, w[1], b[2], b[3]);
        mma16(c1, w[3], b[2], b[3]);
        PUB_F(pdst + 18 * 128 * 32, sel22(c0, c1, t4) + ((t4 & 2) ? ((t4 & 1) ? c2[3] : c2[1]) : ((t4 & 1) ? c2[2] : c2[0])), tag);
        if (warp == 17) TL(25);
    }
    if (owner) {
        const float k = owner_sum<FDELAY>(g_part2[1] + cta * 4096, sb + OFF_OWN, tag, warp, lane);
        if (warp == 0) {
            reinterpret_cast<unsigned short*>(out)[col] = (unsigned short)pack2(x1c + bfr(gg[1] * bfr(bfr(k) + b2c)), 0.f);
            if (tid == 0 && cta == 0) asm volatile("st.relaxed.gpu.global.u32 [%0], %1;" ::"l"(&g_epoch), "r"(epoch + 1) : "memory");
            TL(33);
        }
    }
#undef BAR
}

typedef CUresult (*EncodeFn)(CUtensorMap*, CUtensorMapDataType, cuuint32_t, void*, const cuuint64_t*, const cuuint64_t*,
                             const cuuint32_t*, const cuuint32_t*, CUtensorMapInterleave, CUtensorMapSwizzle,
                             CUtensorMapL2promotion, CUtensorMapFloatOOBfill);

void make_map(EncodeFn enc, CUtensorMap* m, const void* ptr, cuuint64_t d0, cuuint64_t d1, cuuint64_t d2, cuuint64_t s1,
              cuuint64_t s2, cuuint32_t b0, cuuint32_t b1, cuuint32_t b2, bool swz) {
    const cuuint64_t dims[3] = {d0, d1, d2}, str[2] = {s1, s2};
    const cuuint32_t box[3] = {b0, b1, b2}, es[3] = {1, 1, 1};
    enc(m, CU_TENSOR_MAP_DATA_TYPE_BFLOAT16, 3, const_cast<void*>(ptr), dims, str, box, es, CU_TENSOR_MAP_INTERLEAVE_NONE,
        swz ? CU_TENSOR_MAP_SWIZZLE_128B : CU_TENSOR_MAP_SWIZZLE_NONE,
        swz ? CU_TENSOR_MAP_L2_PROMOTION_L2_256B : CU_TENSOR_MAP_L2_PROMOTION_L2_128B, CU_TENSOR_MAP_FLOAT_OOB_FILL_NONE);
}

}

extern "C" void kernel_launch(void* const* d_in, const int* in_sizes, int n_in, void* d_out, int out_size) {
    (void)in_sizes; (void)n_in; (void)out_size;
    static EncodeFn enc = nullptr;
    if (!enc) {
        void* fn = nullptr;
        cudaDriverEntryPointQueryResult st;
        cudaGetDriverEntryPoint("cuTensorMapEncodeTiled", &fn, cudaEnableDefault, &st);
        enc = (EncodeFn)fn;
        cudaFuncSetAttribute(fused_block_kernel, cudaFuncAttributeMaxDynamicSharedMemorySize, SMEM_BYTES);
    }
    Params p;
    make_map(enc, &p.m[0], d_in[11], 576, 576, 6, 3456 * 2, 576 * 2, 72, 36, 2, false);
    make_map(enc, &p.m[1], d_in[3], 64, 576, 64, 4096 * 2, 128, 64, 24, 4, true);
    make_map(enc, &p.m[2], d_in[1], 64, 16ull * SK, 2, 256, 128, 64, 32, 2, true);
    make_map(enc, &p.m[3], d_in[2], 64, 16ull * SK, 2, 256, 128, 64, 32, 2, true);
    make_map(enc, &p.m[4], d_in[4], 64, 4096, 9, 576 * 2, 128, 64, 8, 9, true);
    make_map(enc, &p.m[5], d_in[6], FF, 576, 1, FF * 2, FF * 2 * 576, 40, 96, 1, false);
    make_map(enc, &p.m[6], d_in[8], 64, FF, 9, 576 * 2, 128, 64, 8, 9, true);
    make_map(enc, &p.m[7], d_in[8], 64, FF, 9, 576 * 2, 128, 64, 4, 9, true);
    fused_block_kernel<<<NCTA, NTHREADS, SMEM_BYTES>>>(p, (const __nv_bfloat16*)d_in[0], (const __nv_bfloat16*)d_in[10],
                                                        (const __nv_bfloat16*)d_in[7], (const __nv_bfloat16*)d_in[9],
                                                        (__nv_bfloat16*)d_out);
}
```

```cpp
#include <cuda_runtime.h>
#include <cuda_bf16.h>
#include <cuda.h>
#include <stdint.h>

#define OREP 4
#define CAPN 6

namespace {

constexpr int SK = 32768, WIN = 4096, FF = 4608;
constexpr int NCTA = 128;
constexpr int NCONS = 576;
constexpr int NTHREADS = NCONS + 64;

constexpr int OFF_K = 0;
constexpr int OFF_M = 131072;
constexpr int OFF_WQ = OFF_M + 31744;
constexpr int OFF_VA = 201728;
constexpr int OFF_VB = 136192;
constexpr int OFF_VC = 0;
constexpr int OFF_WO = 49152;
constexpr int OFF_W1 = OFF_WO + 40960;
constexpr int OFF_W2 = OFF_VB;
constexpr int OFF_MISC = OFF_VA + 16384;
constexpr int OFF_BAR = OFF_MISC;
constexpr int OFF_S = OFF_BAR + 448;
constexpr int OFF_H = OFF_S + 128;
constexpr int OFF_WGT = OFF_H + 192;
constexpr int OFF_HH = OFF_WGT + 128;
constexpr int OFF_Q = OFF_HH + 128;
constexpr int OFF_P = OFF_Q + 512;
constexpr int OFF_XN = OFF_P + 2048;
constexpr int OFF_ST = OFF_XN + 2304;
constexpr int OFF_WMX = OFF_ST + 4608;
constexpr int OFF_WSM = OFF_WMX + 128;
constexpr int OFF_OWN = OFF_P;
constexpr int OFF_COEF = OFF_WSM + 128;
constexpr int SMEM_BYTES = OFF_COEF + 32;
constexpr int OFF_REDO = OFF_XN;
constexpr int OFF_FB = OFF_VC;
constexpr int OFF_RED = OFF_VC + 8192;
static_assert(SMEM_BYTES <= 232448, "smem");
static_assert(OFF_W1 + 46080 <= OFF_VB, "w1");

enum { G_M = 0, G_WQ = 3, G_K = 6, G_V = 22, G_WO = 38, G_W1 = 42, G_W2 = 48, NFULL = 51, E_B = NFULL, E_S, E_V, R_HH, NBAR };
static_assert(NBAR <= 56, "bars");

struct Sched { int t_wq, d_wq, t_kv, d_kv, t_wo, d_wo, t_w1, d_w1, t_w2, d_w2, t_a, t_x, t_f; };
constexpr Sched SCHED = {684, 516, 2232, 344, 13450, 340, 14900, 310, 16850, 412, 15170, 17170, 19630};
#define SCH(f) SCHED.f
#define SCH_PARAM
#define SCH_WPARAM
#define SCH_WARG
#define SCH_ARG
#define SCHW(f) SCHED.f

struct Scratch {
    float row[128][704];
    float modF[4 * 576];
    float partA[128][256];
    float partO[8 * OREP][576];
    float partF[18 * 128 * 32];
    unsigned epoch;
};
__device__ __align__(128) Scratch g_scratch;

#define TL(i) do { } while (0)

struct Params { CUtensorMap m[8]; };

constexpr unsigned SPIN_LIMIT = 1u << 22;

__device__ __forceinline__ void mbar_init(uint32_t bar, int cnt) {
    asm volatile("mbarrier.init.shared::cta.b64 [%0], %1;" ::"r"(bar), "r"(cnt) : "memory");
}
__device__ __forceinline__ void mbar_expect(uint32_t bar, uint32_t bytes) {
    asm volatile("mbarrier.arrive.expect_tx.shared::cta.b64 _, [%0], %1;" ::"r"(bar), "r"(bytes) : "memory");
}
__device__ __forceinline__ void mbar_arrive(uint32_t bar) {
    asm volatile("mbarrier.arrive.shared::cta.b64 _, [%0];" ::"r"(bar) : "memory");
}
__device__ __forceinline__ void mbar_wait(uint32_t bar) {
    asm volatile("{\n.reg .pred p;\n.reg .u32 n;\nmov.u32 n, 0;\n"
                 "W_%=:\nmbarrier.try_wait.parity.shared::cta.b64 p, [%0], 0;\n@p bra D_%=;\n"
                 "add.u32 n, n, 1;\nsetp.lt.u32 p, n, 4000000;\n@p bra W_%=;\ntrap;\nD_%=:\n}"
                 ::"r"(bar) : "memory");
}
__device__ __forceinline__ bool mbar_test(uint32_t bar) {
    uint32_t ok;
    asm volatile("{\n.reg .pred p;\nmbarrier.test_wait.parity.shared::cta.b64 p, [%1], 0;\nselp.u32 %0, 1, 0, p;\n}" : "=r"(ok) : "r"(bar) : "memory");
    return __all_sync(~0u, ok);
}
__device__ __forceinline__ void tma3(uint32_t dst, const CUtensorMap* m, int c0, int c1, int c2, uint32_t bar, uint64_t pol) {
    asm volatile("cp.async.bulk.tensor.3d.shared::cluster.global.mbarrier::complete_tx::bytes.L2::cache_hint "
                 "[%0], [%1, {%3, %4, %5}], [%2], %6;"
                 ::"r"(dst), "l"(m), "r"(bar), "r"(c0), "r"(c1), "r"(c2), "l"(pol) : "memory");
}
__device__ __forceinline__ uint32_t gtime() { uint32_t t; asm volatile("mov.u32 %0, %globaltimer_lo;" : "=r"(t)); return t; }
__device__ __forceinline__ bool elect() {
    uint32_t p; asm volatile("{\n.reg .pred p;\nelect.sync _|p, 0xffffffff;\nselp.u32 %0, 1, 0, p;\n}" : "=r"(p)); return p;
}
__device__ __forceinline__ void bar_sync(int id, int n) { asm volatile("bar.sync %0, %1;" ::"r"(id), "r"(n) : "memory"); }
__device__ __forceinline__ void bar_arrive(int id, int n) { asm volatile("bar.arrive %0, %1;" ::"r"(id), "r"(n) : "memory"); }

__device__ __forceinline__ void ldsm4(uint32_t (&r)[4], uint32_t a) {
    asm volatile("ldmatrix.sync.aligned.m8n8.x4.shared.b16 {%0,%1,%2,%3}, [%4];"
                 : "=r"(r[0]), "=r"(r[1]), "=r"(r[2]), "=r"(r[3]) : "r"(a) : "memory");
}
__device__ __forceinline__ void ldsm4t(uint32_t (&r)[4], uint32_t a) {
    asm volatile("ldmatrix.sync.aligned.m8n8.x4.trans.shared.b16 {%0,%1,%2,%3}, [%4];"
                 : "=r"(r[0]), "=r"(r[1]), "=r"(r[2]), "=r"(r[3]) : "r"(a) : "memory");
}
__device__ __forceinline__ void ldsm2t(uint32_t& r0, uint32_t& r1, uint32_t a) {
    asm volatile("ldmatrix.sync.aligned.m8n8.x2.trans.shared.b16 {%0,%1}, [%2];"
                 : "=r"(r0), "=r"(r1) : "r"(a) : "memory");
}
__device__ __forceinline__ void mma16(float (&c)[4], const uint32_t (&a)[4], uint32_t b0, uint32_t b1) {
    asm volatile("mma.sync.aligned.m16n8k16.row.col.f32.bf16.bf16.f32 {%0,%1,%2,%3}, {%4,%5,%6,%7}, {%8,%9}, {%0,%1,%2,%3};"
                 : "+f"(c[0]), "+f"(c[1]), "+f"(c[2]), "+f"(c[3])
                 : "r"(a[0]), "r"(a[1]), "r"(a[2]), "r"(a[3]), "r"(b0), "r"(b1));
}
__device__ __forceinline__ void mma8(float (&c)[4], uint32_t a0, uint32_t a1, uint32_t b0) {
    asm volatile("mma.sync.aligned.m16n8k8.row.col.f32.bf16.bf16.f32 {%0,%1,%2,%3}, {%4,%5}, {%6}, {%0,%1,%2,%3};"
                 : "+f"(c[0]), "+f"(c[1]), "+f"(c[2]), "+f"(c[3]) : "r"(a0), "r"(a1), "r"(b0));
}
__device__ __forceinline__ uint32_t lds32(uint32_t a) {
    uint32_t v; asm volatile("ld.shared.b32 %0, [%1];" : "=r"(v) : "r"(a) : "memory"); return v;
}
__device__ __forceinline__ float ldsf(uint32_t a) {
    float v; asm volatile("ld.shared.f32 %0, [%1];" : "=f"(v) : "r"(a) : "memory"); return v;
}
__device__ __forceinline__ void ldsf2(float& x, float& y, uint32_t a) {
    asm volatile("ld.shared.v2.f32 {%0,%1}, [%2];" : "=f"(x), "=f"(y) : "r"(a) : "memory");
}
__device__ __forceinline__ void ldsf4(float (&r)[4], uint32_t a) {
    asm volatile("ld.shared.v4.f32 {%0,%1,%2,%3}, [%4];" : "=f"(r[0]), "=f"(r[1]), "=f"(r[2]), "=f"(r[3]) : "r"(a) : "memory");
}
__device__ __forceinline__ void lds128(uint32_t (&r)[4], uint32_t a) {
    asm volatile("ld.shared.v4.b32 {%0,%1,%2,%3}, [%4];" : "=r"(r[0]), "=r"(r[1]), "=r"(r[2]), "=r"(r[3]) : "r"(a) : "memory");
}
__device__ __forceinline__ void stsf(uint32_t a, float v) { asm volatile("st.shared.f32 [%0], %1;" ::"r"(a), "f"(v) : "memory"); }
__device__ __forceinline__ void stsf2(uint32_t a, float x, float y) { asm volatile("st.shared.v2.f32 [%0], {%1,%2};" ::"r"(a), "f"(x), "f"(y) : "memory"); }
__device__ __forceinline__ void sts16(uint32_t a, uint32_t v) { asm volatile("st.shared.b16 [%0], %1;" ::"r"(a), "h"((unsigned short)v) : "memory"); }
__device__ __forceinline__ void sts32(uint32_t a, uint32_t v) { asm volatile("st.shared.b32 [%0], %1;" ::"r"(a), "r"(v) : "memory"); }
__device__ __forceinline__ uint32_t pack2(float lo, float hi) {
    uint32_t d; asm("cvt.rn.bf16x2.f32 %0, %1, %2;" : "=r"(d) : "f"(hi), "f"(lo)); return d;
}
__device__ __forceinline__ float bfr(float x) { return __uint_as_float(pack2(0.f, x)); }
__device__ __forceinline__ float fsqrt(float x) { float r; asm("sqrt.approx.ftz.f32 %0, %1;" : "=f"(r) : "f"(x)); return r; }
__device__ __forceinline__ float frcp(float x) { float r; asm("rcp.approx.ftz.f32 %0, %1;" : "=f"(r) : "f"(x)); return r; }
__device__ __forceinline__ float fexp(float x) { float r; asm("ex2.approx.ftz.f32 %0, %1;" : "=f"(r) : "f"(x * 1.4426950408889634f)); return r; }
__device__ __forceinline__ float ln_rden(float var) { return frcp(bfr(fsqrt(bfr(bfr(fmaxf(var, 0.f)) + 1e-5f)))); }
__device__ __forceinline__ int fpos(int k) { return (k & ~31) | ((k & 6) << 2) | ((k >> 2) & 6) | (k & 1); }
__device__ __forceinline__ void stsv(uint32_t base, int k, float v) {
    asm volatile("st.shared.b16 [%0], %1;" ::"r"(base + fpos(k) * 2), "h"((unsigned short)pack2(v, 0.f)) : "memory");
}
__device__ __forceinline__ float ldbf(const __nv_bfloat16* p) {
    return __uint_as_float((uint32_t)__ldg(reinterpret_cast<const unsigned short*>(p)) << 16);
}
__device__ __forceinline__ float sel4(const float (&c)[4], int t) { return (t & 2) ? ((t & 1) ? c[3] : c[2]) : ((t & 1) ? c[1] : c[0]); }
__device__ __forceinline__ float sel22(const float (&c0)[4], const float (&c1)[4], int t) {
    return (t & 2) ? ((t & 1) ? c1[2] : c1[0]) : ((t & 1) ? c0[2] : c0[0]);
}

__device__ __forceinline__ float untag(uint32_t u) { return __uint_as_float(u & ~3u); }
__device__ __forceinline__ void clr(float* p) { asm volatile("st.relaxed.gpu.global.b32 [%0], %1;" ::"l"(p), "r"(0) : "memory"); }
__device__ __forceinline__ void pub(float* p, float a, uint32_t tag) {
    asm volatile("{\n.reg .b32 o;\natom.relaxed.gpu.global.exch.b32 o, [%0], %1;\n}"
                 ::"l"(p), "r"((__float_as_uint(a) & ~3u) | tag) : "memory");
}
__device__ __forceinline__ void pubst(float* p, float a, uint32_t tag) {
    asm volatile("st.relaxed.gpu.global.b32 [%0], %1;" ::"l"(p), "r"((__float_as_uint(a) & ~3u) | tag) : "memory");
}
template <int OFF>
__device__ __forceinline__ void ldp(uint32_t& u, const float* p, uint32_t tag) {
    asm volatile("{\n.reg .pred p;\n.reg .b32 t;\nlop3.b32 t, %0, %2, 3, 0x28;\nsetp.ne.u32 p, t, 0;\n"
                 "@p ld.relaxed.gpu.global.b32 %0, [%1+%3];\n}" : "+r"(u) : "l"(p), "r"(tag), "n"(OFF) : "memory");
}
template <int N, int STRIDE, int I = 0>
__device__ __forceinline__ void ldp_all(uint32_t (&u)[N], const float* p, uint32_t tag) {
    if constexpr (I < N) { ldp<I * STRIDE * 4>(u[I], p, tag); ldp_all<N, STRIDE, I + 1>(u, p, tag); }
}
template <int N, int STRIDE>
__device__ __forceinline__ void poll(const float* p, uint32_t tag, float (&v)[N]) {
    uint32_t u[N];
#pragma unroll
    for (int i = 0; i < N; i++) u[i] = 0;
    unsigned it = 0;
#pragma unroll 1
    while (true) {
        ldp_all<N, STRIDE>(u, p, tag);
        uint32_t bad = 0;
#pragma unroll
        for (int i = 0; i < N; i++) asm("lop3.b32 %0, %0, %1, %2, 0xf6;" : "+r"(bad) : "r"(u[i]), "r"(tag));
        if (!(bad & 3)) break;
        if (++it > SPIN_LIMIT) __trap();
    }
#pragma unroll
    for (int i = 0; i < N; i++) v[i] = untag(u[i]);
}
template <int OFF>
__device__ __forceinline__ void ldp4(uint32_t (&u)[4], uint32_t bad, const float* p) {
    asm volatile("{\n.reg .pred p;\n.reg .b32 t;\nand.b32 t, %5, 3;\nsetp.ne.u32 p, t, 0;\n"
                 "@p ld.relaxed.gpu.global.v4.b32 {%0,%1,%2,%3}, [%4+%6];\n}"
                 : "+r"(u[0]), "+r"(u[1]), "+r"(u[2]), "+r"(u[3]) : "l"(p), "r"(bad), "n"(OFF) : "memory");
}
template <int N>
__device__ __forceinline__ float tree_sum(float (&v)[N]) {
#pragma unroll
    for (int s = 1; s < N; s *= 2)
#pragma unroll
        for (int i = 0; i + s < N; i += 2 * s) v[i] += v[i + s];
    return v[0];
}
__device__ __forceinline__ float xadd(float keep, float send, int o) { return keep + __shfl_xor_sync(~0u, send, o); }

__device__ __forceinline__ void sum6_warp(const float (&v)[6], uint32_t st, int warp, int lane) {
    const bool b4 = lane & 16, b3 = lane & 8, b2 = lane & 4;
    const float w0 = xadd(b4 ? v[3] : v[0], b4 ? v[0] : v[3], 16);
    const float w1 = xadd(b4 ? v[4] : v[1], b4 ? v[1] : v[4], 16);
    const float w2 = xadd(b4 ? v[5] : v[2], b4 ? v[2] : v[5], 16);
    const float z0 = xadd(b3 ? w1 : w0, b3 ? w0 : w1, 8);
    const float z1 = xadd(w2, w2, 8);
    float t = xadd(b2 ? z1 : z0, b2 ? z0 : z1, 4);
    t = xadd(t, t, 2);
    t = xadd(t, t, 1);
    if (!(lane & 3)) stsf(st + (lane >> 2) * 192 + warp * 4, t);
}
__device__ __forceinline__ void sum6_total(float (&v)[6], uint32_t st, int lane) {
    const uint32_t row = st + (lane >> 2) * 192;
    float q[4];
    ldsf4(q, row + (lane & 3) * 16);
    const float e = ldsf(row + 64 + (lane & 1) * 4);
    float t = (q[0] + q[1]) + (q[2] + q[3]) + ((lane & 2) ? 0.f : e);
    t = xadd(t, t, 1);
    t = xadd(t, t, 2);
    v[0] = __shfl_sync(~0u, t, 0);  v[1] = __shfl_sync(~0u, t, 8);  v[2] = __shfl_sync(~0u, t, 4);
    v[3] = __shfl_sync(~0u, t, 16); v[4] = __shfl_sync(~0u, t, 24); v[5] = __shfl_sync(~0u, t, 20);
}

__device__ __forceinline__ void owner_part(const float* part, uint32_t own, uint32_t tag, int warp, int lane) {
    const float* p = part + warp * 256 + lane * 4;
    uint32_t u[4] = {0, 0, 0, 0}, w[4] = {0, 0, 0, 0}, bu = 1, bw = 1;
    unsigned it = 0;
#pragma unroll 1
    while (true) {
        ldp4<0>(u, bu, p);
        ldp4<512>(w, bw, p);
        bu = (u[0] ^ tag) | (u[1] ^ tag) | (u[2] ^ tag) | (u[3] ^ tag);
        bw = (w[0] ^ tag) | (w[1] ^ tag) | (w[2] ^ tag) | (w[3] ^ tag);
        if (!((bu | bw) & 3)) break;
        if (++it > SPIN_LIMIT) __trap();
    }
    float s[4];
#pragma unroll
    for (int i = 0; i < 4; i++) s[i] = untag(u[i]) + untag(w[i]);
    const bool hi = lane & 16, h8 = lane & 8;
    const float k0 = xadd(hi ? s[2] : s[0], hi ? s[0] : s[2], 16);
    const float k1 = xadd(hi ? s[3] : s[1], hi ? s[1] : s[3], 16);
    const float k = xadd(h8 ? k1 : k0, h8 ? k0 : k1, 8);
    stsf(own + (((lane & 7) * 4 + (lane >> 4) * 2 + ((lane >> 3) & 1)) * 20 + warp) * 4, k);
}

#define BAR(i) (bars + (i) * 8)
__device__ __noinline__ void worker(Scratch* __restrict__ sc, uint32_t ttop, unsigned epoch, uint32_t xraw, uint32_t craw,
                                    const __nv_bfloat16* __restrict__ b1, const __nv_bfloat16* __restrict__ b2,
                                    __nv_bfloat16* __restrict__ out SCH_WPARAM) {
    extern __shared__ __align__(1024) unsigned char smem[];
    const uint32_t sb = (uint32_t)__cvta_generic_to_shared(smem);
    const int tid = threadIdx.x, warp = __shfl_sync(~0u, tid >> 5, 0), lane = tid & 31;
    const int cta = blockIdx.x, g = cta >> 3, r = cta & 7;
    const uint32_t bars = sb + OFF_BAR;
    const int gq = lane >> 2, t4 = lane & 3;

    if (warp == 19) {
        const int e = 24 * g + lane;
        float* const mdst = sc->modF + (e / 72) * 576 + 72 * r + e % 72;
        if (g < 12 && lane < 24) clr(mdst);
        const uint32_t tag = 1 + (epoch & 1);
        bar_sync(5, NTHREADS);
        mbar_wait(BAR(G_K + 4));
        if (g < 12 && lane < 24) {
            float v[16];
            poll<16, 8 * 704>(sc->row[r] + 144 + e, tag, v);
            pub(mdst, bfr(tree_sum(v)), tag);
        }
        __syncwarp();
        bar_sync(3, 512 + 32);
        {
            float m = ldsf(sb + OFF_WMX + lane * 4), l = ldsf(sb + OFF_WSM + lane * 4);
#pragma unroll
            for (int o = 2; o <= 16; o <<= 1) { m = fmaxf(m, __shfl_xor_sync(~0u, m, o)); l += __shfl_xor_sync(~0u, l, o); }
            if (lane < 8) pub(sc->row[cta] + 432 + lane, (lane & 2) ? l : m, tag);
            mbar_wait(BAR(G_V + 8));
            float v[2];
            poll<2, 2>(sc->row[(cta & ~15) + (lane & 15)] + 432 + (lane >> 4), tag, v);
            float mg = v[0];
#pragma unroll
            for (int o = 1; o <= 4; o <<= 1) mg = fmaxf(mg, __shfl_xor_sync(~0u, mg, o));
            const float w = fexp(v[0] - mg);
            float lg = w * v[1];
#pragma unroll
            for (int o = 1; o <= 4; o <<= 1) lg += __shfl_xor_sync(~0u, lg, o);
            stsf(sb + OFF_WGT + lane * 4, w * frcp(lg));
            __syncwarp();
            bar_arrive(4, 512 + 32);
        }
        TL(30);
        float pre[6], v[6];
        bar_sync(9, NCONS + 32);
        sum6_total(pre, sb + OFF_ST + 1536, lane);
        bar_sync(6, NCONS + 32);
        sum6_total(v, sb + OFF_ST + 3072, lane);
        constexpr float RN = 1.f / 576.f;
        const float mean = v[0] * RN, mb = bfr(mean);
        const float r1 = ln_rden(v[1] * RN - mean * mean);
        const float m2 = (r1 * (v[2] - mb * pre[0]) + pre[3]) * RN;
        const float e2 = (r1 * (r1 * (v[3] - mb * (2.f * v[4] - mb * pre[1])) + 2.f * (v[5] - mb * pre[2])) + pre[4]) * RN;
        const float r2 = ln_rden(e2 - m2 * m2), r12 = r1 * r2;
        if (lane < 2) stsf2(sb + OFF_COEF + lane * 8, lane ? -r12 * mb : r12, lane ? r2 : -r2 * bfr(m2));
        __syncwarp();
        bar_arrive(10, 96 + 32);
        TL(34);
        return;
    }

    float* const pdst = sc->partF + (warp * 128 + cta) * 32 + t4 * 8 + gq;
    float* const odst = sc->partO[8 * t4 + (cta >> 4)] + 36 * (cta & 15) + (tid >> 2);
    if (tid < 40) {
        const float cin = __uint_as_float(craw << 16);
        stsv(sb + OFF_S, tid, cin * frcp(1.f + fexp(-cin)));
        stsv(sb + OFF_HH, tid, 0.f);
    }
    const uint32_t tag = 1 + (epoch & 1);
    bar_sync(5, NTHREADS);
    if (warp == 0) TL(8);
    const int mi = lane >> 3, l7 = lane & 7;
    const int krw = l7 + ((lane >> 4) << 3);

    {
        uint32_t b[4];
        lds128(b, sb + OFF_S + t4 * 16);
        const uint32_t bt = lds32(sb + OFF_S + 64 + t4 * 16);
        const int tl = warp < 9 ? warp : warp - 9, cg = 2 * tl + (mi & 1);
        const uint32_t ca = sb + OFF_M + (cg >= 9 ? 5184 - 144 : 0) + cg * 16;
#pragma unroll 1
        for (int u = warp >= 9; u < (warp < 9 ? 1 : 3); u++) {
            mbar_wait(BAR(G_M + u));
            uint32_t a0[4], a1[4], a2, a3;
            ldsm4t(a0, ca + u * 10368 + krw * 144);
            ldsm4t(a1, ca + u * 10368 + krw * 144 + 16 * 144);
            ldsm2t(a2, a3, ca + u * 10368 + min(32 + l7, 35) * 144);
            float c[4] = {0.f, 0.f, 0.f, 0.f};
            mma16(c, a0, b[0], b[1]);
            mma16(c, a1, b[2], b[3]);
            mma8(c, a2, a3, bt);
            if (t4 < 2) pub(sc->row[cta] + u * 144 + tl * 16 + t4 * 8 + gq, t4 ? c[2] : c[0], tag);
        }
        if (warp == 0) TL(10);
    }
    if (tid < 256) clr(sc->partA[cta] + tid);
    if (tid < 144) clr(odst);
    clr(pdst);
    float b2c = 0.f, b1v = 0.f;
    const int unit = (tid >> 1) - (cta & 1) * 4;
    if (unit >= 0 && unit < 36) b1v = ldbf(b1 + 36 * cta + unit);
    if (warp == cta) b2c = ldbf(b2 + tid);
    const float xv = __uint_as_float(xraw << 16);
    {
        float v[6] = {xv, xv * xv, 0.f, 0.f, 0.f, 0.f};
        sum6_warp(v, sb + OFF_ST, warp, lane);
        bar_sync(1, NCONS);
        sum6_total(v, sb + OFF_ST, lane);
        const float mean = v[0] * (1.f / 576.f);
        stsf(sb + OFF_XN + tid * 4, bfr(bfr(xv - bfr(mean)) * ln_rden(v[1] * (1.f / 576.f) - mean * mean)));
        bar_sync(1, NCONS);
    }

    if (warp >= 16) {
        __syncwarp();
        if (lane == 0) mbar_arrive(BAR(E_B));
        mbar_wait(BAR(G_K + 15));
    } else {
        if (tid < 160) {
            float s = 0.f;
            if (tid < 144) {
                float v[16];
                poll<16, 8 * 704>(sc->row[r] + (tid & 1) * 72 + (tid >> 1), tag, v);
                s = bfr(tree_sum(v));
            }
            const float ca = __shfl_xor_sync(~0u, s, 1);
            if (tid < 144 && !(tid & 1))
                stsv(sb + OFF_H, tid >> 1, bfr(ldsf(sb + OFF_XN + (72 * r + (tid >> 1)) * 4) * bfr(1.f + ca)) + s);
        }
        {
            uint32_t a[4][4], a4, a5;
            const uint32_t base = sb + OFF_WQ + (warp >> 2) * 3072 + l7 * 128 + (((2 * (warp & 3) + (mi & 1)) ^ l7) << 4);
            const bool up = lane & 16;
            mbar_wait(BAR(G_WQ));
            ldsm4t(a[0], base + (up ? 1024 : 0));
            mbar_wait(BAR(G_WQ + 1));
            ldsm4t(a[1], base + (up ? 12288 : 2048));
            ldsm4t(a[2], base + (up ? 12288 + 2048 : 12288 + 1024));
            mbar_wait(BAR(G_WQ + 2));
            ldsm4t(a[3], base + (up ? 24576 + 1024 : 24576));
            ldsm2t(a4, a5, base + 24576 + 2048);
            bar_sync(2, 512);
            if (warp == 0) TL(11);
            uint32_t b0[4], b1r[4];
            lds128(b0, sb + OFF_H + t4 * 16);
            lds128(b1r, sb + OFF_H + 64 + t4 * 16);
            const uint32_t bt = lds32(sb + OFF_H + 128 + t4 * 16);
            float c0[4] = {0.f, 0.f, 0.f, 0.f}, c1[4] = {0.f, 0.f, 0.f, 0.f};
            mma16(c0, a[0], b0[0], b0[1]);
            mma16(c1, a[1], b0[2], b0[3]);
            mma16(c0, a[2], b1r[0], b1r[1]);
            mma16(c1, a[3], b1r[2], b1r[3]);
            mma8(c0, a4, a5, bt);
            if (t4 < 2) pub(sc->row[cta] + 448 + warp * 16 + t4 * 8 + gq, t4 ? c0[2] + c1[2] : c0[0] + c1[0], tag);
            if (lane == 0) mbar_arrive(BAR(E_B));
        }
        if (warp == 0) TL(12);
        if (tid < 256) {
            float v[8];
            poll<8, 704>(sc->row[g * 8] + 448 + tid, tag, v);
            stsv(sb + OFF_Q, tid, tree_sum(v));
        }
        bar_sync(2, 512);
        if (warp == 0) TL(13);
        float sco[2];
        {
            uint32_t qb[4][4];
#pragma unroll
            for (int i = 0; i < 4; i++) lds128(qb[i], sb + OFF_Q + (gq & 1) * 256 + i * 64 + t4 * 16);
            mbar_wait(BAR(G_K + warp));
#pragma unroll
            for (int u = 0; u < 2; u++) {
                const uint32_t base = sb + OFF_K + warp * 8192 + (u * 16 + (lane & 15)) * 128;
                float c0[4] = {0.f, 0.f, 0.f, 0.f}, c1[4] = {0.f, 0.f, 0.f, 0.f};
#pragma unroll
                for (int ks = 0; ks < 4; ks++) {
                    const int sw = ((2 * ks + (lane >> 4)) ^ l7) << 4;
                    uint32_t a[4], a2[4];
                    ldsm4(a, base + sw);
                    ldsm4(a2, base + 4096 + sw);
                    mma16(c0, a, qb[ks >> 1][2 * (ks & 1)], qb[ks >> 1][2 * (ks & 1) + 1]);
                    mma16(c1, a2, qb[2 + (ks >> 1)][2 * (ks & 1)], qb[2 + (ks >> 1)][2 * (ks & 1) + 1]);
                }
                sco[u] = bfr(bfr(sel4(c0, t4) + sel4(c1, t4)) * 0.08838834764831845f);
            }
            if (lane == 0) mbar_arrive(BAR(E_S));
            float mx = fmaxf(sco[0], sco[1]);
#pragma unroll
            for (int o = 2; o <= 16; o <<= 1) mx = fmaxf(mx, __shfl_xor_sync(~0u, mx, o));
            if (lane < 2) stsf(sb + OFF_WMX + (warp * 2 + lane) * 4, mx);
        }
        bar_sync(2, 512);
        if (warp == 0) TL(14);
        {
            float m = ldsf(sb + OFF_WMX + lane * 4);
#pragma unroll
            for (int o = 2; o <= 16; o <<= 1) m = fmaxf(m, __shfl_xor_sync(~0u, m, o));
            const float p0 = fexp(sco[0] - m), p1 = fexp(sco[1] - m);
            const int key = warp * 32 + gq + ((t4 & 2) << 2);
            stsv(sb + OFF_P + (t4 & 1) * 1024, key, p0);
            stsv(sb + OFF_P + (t4 & 1) * 1024, key + 16, p1);
            float l = p0 + p1;
#pragma unroll
            for (int o = 2; o <= 16; o <<= 1) l += __shfl_xor_sync(~0u, l, o);
            if (lane < 2) stsf(sb + OFF_WSM + (warp * 2 + lane) * 4, l);
        }
        bar_sync(3, 512 + 32);
        if (warp == 0) TL(15);
    }
    float gav, sv, cv, gbv;
    {
        float v[4];
        poll<4, 576>(sc->modF + tid, tag, v);
        gav = v[0]; sv = v[1]; cv = bfr(1.f + v[2]); gbv = v[3];
        const float pre[6] = {cv, cv * cv, cv * sv, sv, sv * sv, 0.f};
        sum6_warp(pre, sb + OFF_ST + 1536, warp, lane);
        __syncwarp();
        bar_arrive(9, NCONS + 32);
    }
    if (warp < 8) {
        float c0[4] = {0.f, 0.f, 0.f, 0.f}, c1[4] = {0.f, 0.f, 0.f, 0.f};
        const uint32_t voff = sb + (warp >> 2) * 4096 + krw * 128 + (((2 * (warp & 3) + (mi & 1)) ^ l7) << 4);
        const uint32_t pa = sb + OFF_P + (gq & 1) * 1024 + t4 * 16;
#pragma unroll 1
        for (int ck = 0; ck < 16; ck++) {
            const uint32_t src = voff + ck * 8192 + (ck < 2 ? OFF_VA : (ck < 10 ? OFF_VB - 2 * 8192 : OFF_VC - 10 * 8192));
            uint32_t pb[4], a[4], a2[4];
            lds128(pb, pa + ck * 64);
            mbar_wait(BAR(G_V + ck));
            ldsm4t(a, src);
            ldsm4t(a2, src + 2048);
            mma16(c0, a, pb[0], pb[1]);
            mma16(c1, a2, pb[2], pb[3]);
            if (ck == 7 && lane == 0) mbar_arrive(BAR(E_V));
        }
        pub(sc->partA[cta] + warp * 32 + (t4 & 1) * 16 + gq + ((t4 & 2) << 2), sel4(c0, t4) + sel4(c1, t4), tag);
        if (warp == 0) TL(16);
    }
    const uint32_t woff = (lane >> 4) * 9216 + (warp >> 1) * 1024 + l7 * 128 + ((((warp & 1) * 4 + (mi & 1)) ^ l7) << 4);
    if (warp < 16) {
        uint32_t a[5][4], b[4];
        float wt[2][4], v[8];
        bar_sync(4, 512 + 32);
        ldsf4(wt[0], sb + OFF_WGT + (lane & 16) * 4 + (warp & 8) * 4);
        ldsf4(wt[1], sb + OFF_WGT + (lane & 16) * 4 + (warp & 8) * 4 + 16);
        const uint32_t base = sb + OFF_WO + ((warp >> 2) * 128 + (warp & 3) * 16 + krw) * 80;
#define LOAD_WO() do { _Pragma("unroll") for (int i = 0; i < 4; i++) ldsm4t(a[i], base + (i & 1) * 5120 + ((i & 2) + (mi & 1)) * 16); \
                       ldsm4t(a[4], base + (mi & 1) * 5120 + 64); } while (0)
        mbar_wait(BAR(G_V + 15));
        while ((int)(gtime() - ttop) < SCHW(t_a)) {}
        const uint32_t wobar = BAR(G_WO + (warp >> 2));
        bool rdy = false;
        {
            uint32_t u[8] = {0, 0, 0, 0, 0, 0, 0, 0};
            unsigned it = 0;
#pragma unroll 1
            while (true) {
                ldp_all<8, 256>(u, sc->partA[(cta & ~15) + (warp & 8)] + (warp & 7) * 32 + lane, tag);
                if (!rdy && mbar_test(wobar)) { LOAD_WO(); rdy = true; }
                uint32_t bad = 0;
#pragma unroll
                for (int i = 0; i < 8; i++) asm("lop3.b32 %0, %0, %1, %2, 0xf6;" : "+r"(bad) : "r"(u[i]), "r"(tag));
                if (__all_sync(~0u, !(bad & 3))) break;
                if (++it > SPIN_LIMIT) __trap();
            }
#pragma unroll
            for (int i = 0; i < 8; i++) v[i] = untag(u[i]) * wt[i >> 2][i & 3];
        }
        if (warp == 15) TL(31);
        const uint32_t ou = __float_as_uint(bfr(tree_sum(v)));
        const uint32_t pr = (ou >> 16) | __shfl_down_sync(~0u, ou, 1);
#pragma unroll
        for (int j = 0; j < 4; j++) b[j] = __shfl_sync(~0u, pr, 8 * j + 2 * t4);
        if (!rdy) { mbar_wait(wobar); LOAD_WO(); }
        if (warp == 15) TL(18);
        float c0[4] = {0.f, 0.f, 0.f, 0.f}, c1[4] = {0.f, 0.f, 0.f, 0.f}, c2[4] = {0.f, 0.f, 0.f, 0.f};
        mma16(c0, a[0], b[0], b[1]);
        mma16(c1, a[2], b[0], b[1]);
        mma16(c2, a[4], (gq & 1) ? b[2] : b[0], (gq & 1) ? b[3] : b[1]);
        mma16(c0, a[1], b[2], b[3]);
        mma16(c1, a[3], b[2], b[3]);
        const uint32_t red = sb + OFF_REDO + (warp * 56 + gq) * 4;
        stsf(red + t4 * 32, sel22(c0, c1, t4));
        if (t4 == 0) stsf(red + 128, c2[0] + c2[3]);
    }
    bar_sync(1, NCONS);
    if (warp < 5) {
        float v[4];
#pragma unroll
        for (int i = 0; i < 4; i++) v[i] = ldsf(sb + OFF_REDO + ((4 * i + t4) * 56 + (cta & 1) * 4 + (tid >> 2)) * 4);
        float os = tree_sum(v);
        os = xadd(os, os, 1);
        os = xadd(os, os, 2);
        if (tid < 144) pub(odst, os, tag);
    }
    if (warp == 0) TL(19);
    const uint32_t fb = sb + OFF_FB + warp * 320 + fpos(lane) * 2;
    sts16(fb + 128, __float_as_uint(cv) >> 16);
    sts16(fb + 192, __float_as_uint(sv) >> 16);
    sts16(fb + 256, 0x3f80);
    float a;
    {
        uint32_t w[6][4], b[4];
        const uint32_t w1bar = BAR(G_W1 + warp / 3);
        bool w1rdy = false;
#define LOAD_W1() _Pragma("unroll") for (int i = 0; i < 6; i++) \
            ldsm4t(w[i], sb + OFF_W1 + (warp * 32 + (i & 1) * 16 + krw) * 80 + (i < 4 ? ((i & 2) + (mi & 1)) * 16 : 64))
        {
            uint32_t u[8] = {0, 0, 0, 0, 0, 0, 0, 0};
            unsigned it = 0;
#pragma unroll 1
            while (true) {
                if ((int)(gtime() - ttop) >= SCHW(t_x)) ldp_all<8, 576>(u, sc->partO[8 * (cta & (OREP - 1))] + tid, tag);
                if (!w1rdy && mbar_test(w1bar)) { LOAD_W1(); w1rdy = true; }
                uint32_t bad = 0;
#pragma unroll
                for (int i = 0; i < 8; i++) asm("lop3.b32 %0, %0, %1, %2, 0xf6;" : "+r"(bad) : "r"(u[i]), "r"(tag));
                if (__all_sync(~0u, !(bad & 3))) break;
                if (++it > SPIN_LIMIT) __trap();
            }
            float v[8];
#pragma unroll
            for (int i = 0; i < 8; i++) v[i] = untag(u[i]);
            a = bfr(xv + bfr(gav * bfr(tree_sum(v))));
        }
        if (warp == 17) TL(21);
        const float ac = a * cv, hi = bfr(ac);
        sts16(fb, __float_as_uint(hi) >> 16);
        sts16(fb + 64, __float_as_uint(ac - hi) >> 16);
        __syncwarp();
        lds128(b, sb + OFF_FB + warp * 320 + min(gq, 4) * 64 + t4 * 16);
        float c[3][4];
#pragma unroll
        for (int i = 0; i < 3; i++) c[i][0] = c[i][1] = c[i][2] = c[i][3] = 0.f;
#define MMA_W1() do { _Pragma("unroll") for (int i = 0; i < 3; i++) mma16(c[i], w[2 * i], b[0], b[1]); \
                      _Pragma("unroll") for (int i = 0; i < 3; i++) mma16(c[i], w[2 * i + 1], b[2], b[3]); } while (0)
        if (w1rdy) MMA_W1();
        const float v[6] = {a, a * a, ac, ac * ac, ac * cv, ac * sv};
        sum6_warp(v, sb + OFF_ST + 3072, warp, lane);
        __syncwarp();
        bar_arrive(6, NCONS + 32);
        if (!w1rdy) { mbar_wait(w1bar); LOAD_W1(); MMA_W1(); }
        const uint32_t red = sb + OFF_RED + warp * 768 + gq * 16 + t4 * 8;
#pragma unroll
        for (int j = 0; j < 5; j++) {
            const float e0 = c[j >> 1][2 * (j & 1)], e1 = c[j >> 1][2 * (j & 1) + 1];
            const float one = __shfl_down_sync(~0u, e0, 2);
            if (t4 < 2) stsf2(red + j * 128, t4 ? e0 : e0 + e1, t4 ? e1 : one);
        }
        __syncwarp();
        if (warp == 17) TL(22);
        const int trow = (warp >> 1) * 4 + (l7 & 3);
#define LOAD_W2(k) do { ldsm4t(w[k], sb + OFF_W2 + (k) * 18432 + woff); ldsm4t(w[2 + (k)], (sb + OFF_W2 + (k) * 18432 + woff) ^ 32); } while (0)
        if (warp >= 3) {
            bar_arrive(1, NCONS);
        } else {
            bar_sync(1, NCONS);
            if (warp == 0) TL(26);
            float v0[18], v1[18], k0, k1;
#pragma unroll
            for (int i = 0; i < 18; i++) ldsf2(v0[i], v1[i], sb + OFF_RED + i * 768 + tid * 8);
            const float s0 = tree_sum(v0), s1 = tree_sum(v1);
            bar_sync(10, 96 + 32);
            ldsf2(k0, k1, sb + OFF_COEF + (lane & 1) * 8);
            float u = k0 * s0 + k1 * s1;
            u = xadd(u, u, 1);
            u = bfr(bfr(u) + b1v);
            const float z2 = 1.5957691216057308f * (u + 0.044715f * u * u * u);
            u *= frcp(1.f + fexp(-z2));
            if (!(lane & 1) && unit >= 0 && unit < 36) stsv(sb + OFF_HH, unit, u);
            __syncwarp();
            if (lane == 0) mbar_arrive(BAR(R_HH));
            if (warp == 0) TL(27);
        }
        mbar_wait(BAR(G_W2));
        LOAD_W2(0);
        mbar_wait(BAR(G_W2 + 1));
        LOAD_W2(1);
        mbar_wait(BAR(R_HH));
        lds128(b, sb + OFF_HH + t4 * 16);
        const uint32_t bt = lds32(sb + OFF_HH + 64 + t4 * 16);
        float c0[4] = {0.f, 0.f, 0.f, 0.f}, c1[4] = {0.f, 0.f, 0.f, 0.f}, c2[4] = {0.f, 0.f, 0.f, 0.f};
        mma16(c0, w[0], b[0], b[1]);
        mma16(c1, w[2], b[0], b[1]);
        mma16(c0, w[1], b[2], b[3]);
        mma16(c1, w[3], b[2], b[3]);
        mbar_wait(BAR(G_W2 + 2));
        ldsm4t(w[4], sb + OFF_W2 + 36864 + trow * 128 + ((((warp & 1) * 4 + mi) ^ (trow & 7)) << 4));
        if (warp == 17) TL(24);
        mma16(c2, w[4], (gq & 1) ? 0u : bt, (gq & 1) ? bt : 0u);
        pubst(pdst, sel22(c0, c1, t4) + ((t4 & 2) ? ((t4 & 1) ? c2[3] : c2[1]) : ((t4 & 1) ? c2[2] : c2[0])), tag);
        if (warp == 17) TL(25);
    }
    if (cta < 18) {
        while ((int)(gtime() - ttop) < SCHW(t_f)) {}
        if (warp < 16) owner_part(sc->partF + cta * 4096, sb + OFF_OWN, tag, warp, lane);
        if (warp != cta) { bar_arrive(8, NCONS); return; }
        bar_sync(8, NCONS);
        float q[4][4], s[4];
#pragma unroll
        for (int i = 0; i < 4; i++) ldsf4(q[i], sb + OFF_OWN + lane * 80 + i * 16);
#pragma unroll
        for (int i = 0; i < 4; i++) s[i] = (q[i][0] + q[i][1]) + (q[i][2] + q[i][3]);
        const float k = (s[0] + s[1]) + (s[2] + s[3]);
        reinterpret_cast<unsigned short*>(out)[tid] = (unsigned short)pack2(a + bfr(gbv * bfr(bfr(k) + b2c)), 0.f);
        if (tid == 0) asm volatile("st.relaxed.gpu.global.u32 [%0], %1;" ::"l"(&sc->epoch), "r"(epoch + 1) : "memory");
        TL(33);
    }
}

__global__ void __launch_bounds__(NTHREADS, 1)
fused_block_kernel(const __grid_constant__ Params prm, Scratch* __restrict__ sc,
                   const __nv_bfloat16* __restrict__ x_in, const __nv_bfloat16* __restrict__ c_in,
                   const __nv_bfloat16* __restrict__ b1, const __nv_bfloat16* __restrict__ b2,
                   __nv_bfloat16* __restrict__ out SCH_PARAM) {
    const uint32_t ttop = gtime();
    extern __shared__ __align__(1024) unsigned char smem[];
    const uint32_t sb = (uint32_t)__cvta_generic_to_shared(smem);
    const int tid = threadIdx.x, warp = __shfl_sync(~0u, tid >> 5, 0), lane = tid & 31;
    const int cta = blockIdx.x, g = cta >> 3, r = cta & 7;
    const uint32_t bars = sb + OFF_BAR;
    (void)lane;
    if (warp != 18) {
        unsigned epoch;
        asm volatile("ld.relaxed.gpu.global.u32 %0, [%1];" : "=r"(epoch) : "l"(&sc->epoch) : "memory");
        uint32_t xv = 0, cin = 0;
        if (tid < NCONS) asm volatile("ld.global.u16 %0, [%1];" : "=r"(xv) : "l"(x_in + tid) : "memory");
        if (tid < 36) asm volatile("ld.global.u16 %0, [%1];" : "=r"(cin) : "l"(c_in + 36 * g + tid) : "memory");
        if (tid < 176)
            asm volatile("st.relaxed.gpu.global.v4.b32 [%0], {%1,%1,%1,%1};" ::"l"(sc->row[cta] + tid * 4), "r"(0) : "memory");
        bar_sync(11, NTHREADS);
        worker(sc, ttop, epoch, xv, cin, b1, b2, out SCH_WARG);
        return;
    }
    {
        uint64_t pf;
        asm volatile("createpolicy.fractional.L2::evict_first.b64 %0, 1.0;" : "=l"(pf));
        const uint32_t t0 = ttop - 160 + cta * 5 / 2;
        const bool el = elect();
#define TLG() do { } while (0)
#define LOAD(n, dst, map, c0, c1, c2) do { if (el) tma3(sb + (dst), &prm.m[map], c0, c1, c2, BAR(n), pf); TLG(); } while (0)
#define EXPECT(n, bytes) do { if (el) mbar_expect(BAR(n), bytes); } while (0)
#define AT(t) do { } while ((int)(gtime() - t0) < (int)(t))
        const int krow = g * SK + (SK - WIN) + 32 * r;
        if (el) {
#pragma unroll
            for (int i = 0; i < 4; i++) mbar_init(BAR(i), 1);
            asm volatile("fence.proxy.async.shared::cta;" ::: "memory");
        }
        if (el) {
            mbar_expect(BAR(G_M), 10368);     tma3(sb + OFF_M, &prm.m[0], 72 * r, 36 * g, 0, BAR(G_M), pf);
            mbar_expect(BAR(G_WQ), 12288);    tma3(sb + OFF_WQ, &prm.m[1], 0, 72 * r, 4 * g, BAR(G_WQ), pf);
            mbar_expect(BAR(G_M + 1), 10368); tma3(sb + OFF_M + 10368, &prm.m[0], 72 * r, 36 * g, 2, BAR(G_M + 1), pf);
            mbar_expect(BAR(G_M + 2), 10368); tma3(sb + OFF_M + 2 * 10368, &prm.m[0], 72 * r, 36 * g, 4, BAR(G_M + 2), pf);
        }
        __syncwarp();
        bar_arrive(11, NTHREADS);
        if (el) {
            asm volatile("prefetch.tensormap [%0];" ::"l"(&prm.m[2]) : "memory");
#pragma unroll
            for (int i = 4; i < NFULL; i++) mbar_init(BAR(i), 1);
            mbar_init(BAR(E_B), 18);
            mbar_init(BAR(E_S), 16);
            mbar_init(BAR(E_V), 8);
            mbar_init(BAR(R_HH), 3);
            asm volatile("fence.mbarrier_init.release.cluster;" ::: "memory");
            asm volatile("fence.proxy.async.shared::cta;" ::: "memory");
        }
        __syncwarp();
        bar_arrive(5, NTHREADS);
#pragma unroll 1
        for (int i = 1; i < 3; i++) {
            EXPECT(G_WQ + i, 12288);
            AT(SCH(t_wq) + i * SCH(d_wq));
            LOAD(G_WQ + i, OFF_WQ + i * 12288, 1, 0, 72 * r + 24 * i, 4 * g);
        }
        if (el) {
#pragma unroll
            for (int i = 3; i < 8; i++) asm volatile("prefetch.tensormap [%0];" ::"l"(&prm.m[i]) : "memory");
        }
        EXPECT(G_W2, 18432);
        EXPECT(G_W2 + 1, 18432);
        EXPECT(G_W2 + 2, 4608);
#pragma unroll 1
        for (int i = 0; i < 32; i++) {
            EXPECT(G_K + i, 8192);
            if (i == 18) mbar_wait(BAR(E_B));
            if (i == 26) mbar_wait(BAR(E_S));
            mbar_wait(BAR(G_K + i - CAPN));
            const int dst = i * 8192 + (i < 16 ? OFF_K : (i < 18 ? OFF_VA - 16 * 8192 : (i < 26 ? OFF_VB - 18 * 8192 : OFF_VC - 26 * 8192)));
            AT(SCH(t_kv) + i * SCH(d_kv));
            LOAD(G_K + i, dst, 2 + (i >> 4), 0, krow + 256 * ((i + g) & 15), 0);
        }
#pragma unroll 1
        for (int i = 0; i < 4; i++) {
            EXPECT(G_WO + i, 10240);
            mbar_wait(BAR(G_WO + i - CAPN));
            AT(SCH(t_wo) + i * SCH(d_wo));
            LOAD(G_WO + i, OFF_WO + i * 10240, 4, (36 * (cta & 15)) & ~7, 64 * (i & 1), 4 * (cta >> 4) + (i & 2));
        }
#pragma unroll 1
        for (int i = 0; i < 6; i++) {
            EXPECT(G_W1 + i, 7680);
            AT(SCH(t_w1) + i * SCH(d_w1));
            LOAD(G_W1 + i, OFF_W1 + i * 7680, 5, (36 * cta) & ~7, 96 * i, 0);
        }
        mbar_wait(BAR(E_V));
#pragma unroll 1
        for (int i = 0; i < 5; i++) {
            AT(SCH(t_w2) + i * SCH(d_w2));
            LOAD(G_W2 + (i >> 1), OFF_W2 + i * 9216, 6 + (i >> 2), 0, 36 * cta + 8 * i, 0);
        }
        return;
    }
#undef BAR
}

typedef CUresult (*EncodeFn)(CUtensorMap*, CUtensorMapDataType, cuuint32_t, void*, const cuuint64_t*, const cuuint64_t*,
                             const cuuint32_t*, const cuuint32_t*, CUtensorMapInterleave, CUtensorMapSwizzle,
                             CUtensorMapL2promotion, CUtensorMapFloatOOBfill);

void make_map(EncodeFn enc, CUtensorMap* m, const void* ptr, cuuint64_t d0, cuuint64_t d1, cuuint64_t d2, cuuint64_t s1,
              cuuint64_t s2, cuuint32_t b0, cuuint32_t b1, cuuint32_t b2, bool swz) {
    const cuuint64_t dims[3] = {d0, d1, d2}, str[2] = {s1, s2};
    const cuuint32_t box[3] = {b0, b1, b2}, es[3] = {1, 1, 1};
    enc(m, CU_TENSOR_MAP_DATA_TYPE_BFLOAT16, 3, const_cast<void*>(ptr), dims, str, box, es, CU_TENSOR_MAP_INTERLEAVE_NONE,
        swz ? CU_TENSOR_MAP_SWIZZLE_128B : CU_TENSOR_MAP_SWIZZLE_NONE,
        swz ? CU_TENSOR_MAP_L2_PROMOTION_L2_256B : CU_TENSOR_MAP_L2_PROMOTION_L2_128B, CU_TENSOR_MAP_FLOAT_OOB_FILL_NONE);
}

}

extern "C" void kernel_launch(void* const* d_in, const int* in_sizes, int n_in, void* d_out, int out_size) {
    (void)in_sizes; (void)n_in; (void)out_size;
    static EncodeFn enc = nullptr;
    static Scratch* scr = nullptr;
    if (!enc) {
        void* fn = nullptr;
        cudaDriverEntryPointQueryResult st;
        cudaGetDriverEntryPoint("cuTensorMapEncodeTiled", &fn, cudaEnableDefault, &st);
        enc = (EncodeFn)fn;
        cudaGetSymbolAddress((void**)&scr, g_scratch);
        cudaFuncSetAttribute(fused_block_kernel, cudaFuncAttributeMaxDynamicSharedMemorySize, SMEM_BYTES);
    }
    Params p;
    make_map(enc, &p.m[0], d_in[11], 576, 576, 6, 3456 * 2, 576 * 2, 72, 36, 2, false);
    make_map(enc, &p.m[1], d_in[3], 64, 576, 64, 4096 * 2, 128, 64, 24, 4, true);
    make_map(enc, &p.m[2], d_in[1], 64, 16ull * SK, 2, 256, 128, 64, 32, 2, true);
    make_map(enc, &p.m[3], d_in[2], 64, 16ull * SK, 2, 256, 128, 64, 32, 2, true);
    make_map(enc, &p.m[4], d_in[4], 576, 128, 32, 576 * 2, 576 * 2 * 128, 40, 64, 2, false);
    make_map(enc, &p.m[5], d_in[6], FF, 576, 1, FF * 2, FF * 2 * 576, 40, 96, 1, false);
    make_map(enc, &p.m[6], d_in[8], 64, FF, 9, 576 * 2, 128, 64, 8, 9, true);
    make_map(enc, &p.m[7], d_in[8], 64, FF, 9, 576 * 2, 128, 64, 4, 9, true);
    fused_block_kernel<<<NCTA, NTHREADS, SMEM_BYTES>>>(p, scr, (const __nv_bfloat16*)d_in[0], (const __nv_bfloat16*)d_in[10],
                                                        (const __nv_bfloat16*)d_in[7], (const __nv_bfloat16*)d_in[9],
                                                        (__nv_bfloat16*)d_out SCH_ARG);
}
```

```cpp
#include <cuda_runtime.h>
#include <cuda_bf16.h>
#include <cuda.h>
#include <stdint.h>

#define OREP 4
#define CAPN 6

namespace {

constexpr int SK = 32768, WIN = 4096, FF = 4608;
constexpr int NCTA = 128;
constexpr int NCONS = 576;
constexpr int NTHREADS = NCONS + 64;

constexpr int OFF_K = 0;
constexpr int OFF_M = 131072;
constexpr int OFF_WQ = OFF_M + 32768;
constexpr int OFF_VA = 201728;
constexpr int OFF_VB = 136192;
constexpr int OFF_VC = 0;
constexpr int OFF_WO = 49152;
constexpr int OFF_W1 = OFF_WO + 65536;
constexpr int OFF_W2A = OFF_W1 + 73728;
constexpr int OFF_W2B = 0;
constexpr int OFF_MISC = OFF_VA + 16384;
constexpr int OFF_BAR = OFF_MISC;
constexpr int OFF_WGT = OFF_BAR + 512;
constexpr int OFF_HH = OFF_WGT + 128;
constexpr int OFF_P = OFF_HH + 128;
constexpr int OFF_S = OFF_P + 2048;
constexpr int OFF_H = OFF_S + 128;
constexpr int OFF_Q = OFF_H + 192;
constexpr int OFF_XN = OFF_Q + 512;
constexpr int OFF_ST = OFF_XN + 2304;
constexpr int OFF_WMX = OFF_ST + 4608;
constexpr int OFF_WSM = OFF_WMX + 128;
constexpr int OFF_COEF = OFF_WSM + 128;
constexpr int SMEM_BYTES = OFF_COEF + 32;
constexpr int OFF_REDO = OFF_S;
constexpr int OFF_OWN = OFF_P;
constexpr int OFF_FB = OFF_WO;
constexpr int OFF_RED = OFF_WO + 8192;
static_assert(SMEM_BYTES <= 232448, "smem");
static_assert(OFF_W2A + 3 * 9216 <= OFF_MISC && OFF_REDO + 16 * 72 * 4 <= OFF_ST + 1536, "smem");

enum { G_M = 0, G_WQ = 2, G_K = 5, G_V = 21, G_WO = 37, G_W1 = 41, G_W2 = 47, NFULL = 52, E_B = NFULL, E_S, E_V, E_P, R_HH, NBAR };
static_assert(NBAR <= 64, "bars");
__device__ __forceinline__ int mod_pos(int j) { return ((j >> 6) & 7) * 736 + (j >> 9) * 64 + (j & 63); }
__device__ __forceinline__ int wo_tile(int cta) { const int c = cta & 15; return (c & 1) ? c >> 1 : (c == 0 ? 8 : -1); }
__device__ __forceinline__ int mlp_cta(int j) { const int c = j % 9; return 16 * (j / 9) + (c == 8 ? 15 : 2 * c); }
__device__ __forceinline__ int mlp_slot(int cta) { const int c = cta & 15; return (c & 1) ? (c == 15 ? 9 * (cta >> 4) + 8 : -1) : 9 * (cta >> 4) + (c >> 1); }

constexpr int T_WQ = 1184, D_WQ = 572, T_KV = 2898, D_KV = 333, T_WO = 12990, D_WO = 172, T_W1 = 14430, D_W1 = 137,
              T_W2 = 16085, D_W2 = 228, T_A = 14300, T_X = 16250, T_F = 18825;

struct Scratch {
    float row[128][736];
    float modF[4 * 576];
    float partA[128][256];
    float partO[8 * OREP][576];
    unsigned epoch;
};
__device__ __align__(128) Scratch g_scratch;

struct Params { CUtensorMap m[7]; };

constexpr unsigned SPIN_LIMIT = 1u << 22;

__device__ __forceinline__ void mbar_init(uint32_t bar, int cnt) {
    asm volatile("mbarrier.init.shared::cta.b64 [%0], %1;" ::"r"(bar), "r"(cnt) : "memory");
}
__device__ __forceinline__ void mbar_expect(uint32_t bar, uint32_t bytes) {
    asm volatile("mbarrier.arrive.expect_tx.shared::cta.b64 _, [%0], %1;" ::"r"(bar), "r"(bytes) : "memory");
}
__device__ __forceinline__ void mbar_arrive(uint32_t bar) {
    asm volatile("mbarrier.arrive.shared::cta.b64 _, [%0];" ::"r"(bar) : "memory");
}
__device__ __forceinline__ void mbar_wait(uint32_t bar) {
    asm volatile("{\n.reg .pred p;\n.reg .u32 n;\nmov.u32 n, 0;\n"
                 "W_%=:\nmbarrier.try_wait.parity.shared::cta.b64 p, [%0], 0;\n@p bra D_%=;\n"
                 "add.u32 n, n, 1;\nsetp.lt.u32 p, n, 500000;\n@p bra W_%=;\ntrap;\nD_%=:\n}"
                 ::"r"(bar) : "memory");
}
__device__ __forceinline__ bool mbar_test(uint32_t bar) {
    uint32_t ok;
    asm volatile("{\n.reg .pred p;\nmbarrier.test_wait.parity.shared::cta.b64 p, [%1], 0;\nselp.u32 %0, 1, 0, p;\n}" : "=r"(ok) : "r"(bar) : "memory");
    return __all_sync(~0u, ok);
}
__device__ __forceinline__ void tma3(uint32_t dst, const CUtensorMap* m, int c0, int c1, int c2, uint32_t bar, uint64_t pol) {
    asm volatile("cp.async.bulk.tensor.3d.shared::cluster.global.mbarrier::complete_tx::bytes.L2::cache_hint "
                 "[%0], [%1, {%3, %4, %5}], [%2], %6;"
                 ::"r"(dst), "l"(m), "r"(bar), "r"(c0), "r"(c1), "r"(c2), "l"(pol) : "memory");
}
__device__ __forceinline__ uint32_t gtime() { uint32_t t; asm volatile("mov.u32 %0, %globaltimer_lo;" : "=r"(t)); return t; }
__device__ __forceinline__ bool elect() {
    uint32_t p; asm volatile("{\n.reg .pred p;\nelect.sync _|p, 0xffffffff;\nselp.u32 %0, 1, 0, p;\n}" : "=r"(p)); return p;
}
__device__ __forceinline__ void bar_sync(int id, int n) { asm volatile("bar.sync %0, %1;" ::"r"(id), "r"(n) : "memory"); }
__device__ __forceinline__ void bar_arrive(int id, int n) { asm volatile("bar.arrive %0, %1;" ::"r"(id), "r"(n) : "memory"); }

__device__ __forceinline__ void ldsm4(uint32_t (&r)[4], uint32_t a) {
    asm volatile("ldmatrix.sync.aligned.m8n8.x4.shared.b16 {%0,%1,%2,%3}, [%4];"
                 : "=r"(r[0]), "=r"(r[1]), "=r"(r[2]), "=r"(r[3]) : "r"(a) : "memory");
}
__device__ __forceinline__ void ldsm4t(uint32_t (&r)[4], uint32_t a) {
    asm volatile("ldmatrix.sync.aligned.m8n8.x4.trans.shared.b16 {%0,%1,%2,%3}, [%4];"
                 : "=r"(r[0]), "=r"(r[1]), "=r"(r[2]), "=r"(r[3]) : "r"(a) : "memory");
}
__device__ __forceinline__ void ldsm2t(uint32_t& r0, uint32_t& r1, uint32_t a) {
    asm volatile("ldmatrix.sync.aligned.m8n8.x2.trans.shared.b16 {%0,%1}, [%2];"
                 : "=r"(r0), "=r"(r1) : "r"(a) : "memory");
}
__device__ __forceinline__ void mma16(float (&c)[4], const uint32_t (&a)[4], uint32_t b0, uint32_t b1) {
    asm volatile("mma.sync.aligned.m16n8k16.row.col.f32.bf16.bf16.f32 {%0,%1,%2,%3}, {%4,%5,%6,%7}, {%8,%9}, {%0,%1,%2,%3};"
                 : "+f"(c[0]), "+f"(c[1]), "+f"(c[2]), "+f"(c[3])
                 : "r"(a[0]), "r"(a[1]), "r"(a[2]), "r"(a[3]), "r"(b0), "r"(b1));
}
__device__ __forceinline__ void mma8(float (&c)[4], uint32_t a0, uint32_t a1, uint32_t b0) {
    asm volatile("mma.sync.aligned.m16n8k8.row.col.f32.bf16.bf16.f32 {%0,%1,%2,%3}, {%4,%5}, {%6}, {%0,%1,%2,%3};"
                 : "+f"(c[0]), "+f"(c[1]), "+f"(c[2]), "+f"(c[3]) : "r"(a0), "r"(a1), "r"(b0));
}
__device__ __forceinline__ uint32_t lds32(uint32_t a) {
    uint32_t v; asm volatile("ld.shared.b32 %0, [%1];" : "=r"(v) : "r"(a) : "memory"); return v;
}
__device__ __forceinline__ float ldsf(uint32_t a) {
    float v; asm volatile("ld.shared.f32 %0, [%1];" : "=f"(v) : "r"(a) : "memory"); return v;
}
__device__ __forceinline__ void ldsf2(float& x, float& y, uint32_t a) {
    asm volatile("ld.shared.v2.f32 {%0,%1}, [%2];" : "=f"(x), "=f"(y) : "r"(a) : "memory");
}
__device__ __forceinline__ void ldsf4(float (&r)[4], uint32_t a) {
    asm volatile("ld.shared.v4.f32 {%0,%1,%2,%3}, [%4];" : "=f"(r[0]), "=f"(r[1]), "=f"(r[2]), "=f"(r[3]) : "r"(a) : "memory");
}
__device__ __forceinline__ void lds128(uint32_t (&r)[4], uint32_t a) {
    asm volatile("ld.shared.v4.b32 {%0,%1,%2,%3}, [%4];" : "=r"(r[0]), "=r"(r[1]), "=r"(r[2]), "=r"(r[3]) : "r"(a) : "memory");
}
__device__ __forceinline__ void stsf(uint32_t a, float v) { asm volatile("st.shared.f32 [%0], %1;" ::"r"(a), "f"(v) : "memory"); }
__device__ __forceinline__ void stsf2(uint32_t a, float x, float y) { asm volatile("st.shared.v2.f32 [%0], {%1,%2};" ::"r"(a), "f"(x), "f"(y) : "memory"); }
__device__ __forceinline__ void sts16(uint32_t a, uint32_t v) { asm volatile("st.shared.b16 [%0], %1;" ::"r"(a), "h"((unsigned short)v) : "memory"); }
__device__ __forceinline__ uint32_t pack2(float lo, float hi) {
    uint32_t d; asm("cvt.rn.bf16x2.f32 %0, %1, %2;" : "=r"(d) : "f"(hi), "f"(lo)); return d;
}
__device__ __forceinline__ float bfr(float x) { return __uint_as_float(pack2(0.f, x)); }
__device__ __forceinline__ float fsqrt(float x) { float r; asm("sqrt.approx.ftz.f32 %0, %1;" : "=f"(r) : "f"(x)); return r; }
__device__ __forceinline__ float frcp(float x) { float r; asm("rcp.approx.ftz.f32 %0, %1;" : "=f"(r) : "f"(x)); return r; }
__device__ __forceinline__ float fexp(float x) { float r; asm("ex2.approx.ftz.f32 %0, %1;" : "=f"(r) : "f"(x * 1.4426950408889634f)); return r; }
__device__ __forceinline__ float ln_rden(float var) { return frcp(bfr(fsqrt(bfr(bfr(fmaxf(var, 0.f)) + 1e-5f)))); }
__device__ __forceinline__ int fpos(int k) { return (k & ~31) | ((k & 6) << 2) | ((k >> 2) & 6) | (k & 1); }
__device__ __forceinline__ void stsv(uint32_t base, int k, float v) {
    asm volatile("st.shared.b16 [%0], %1;" ::"r"(base + fpos(k) * 2), "h"((unsigned short)pack2(v, 0.f)) : "memory");
}
__device__ __forceinline__ float ldbf(const __nv_bfloat16* p) {
    return __uint_as_float((uint32_t)__ldg(reinterpret_cast<const unsigned short*>(p)) << 16);
}
__device__ __forceinline__ float sel4(const float (&c)[4], int t) { return (t & 2) ? ((t & 1) ? c[3] : c[2]) : ((t & 1) ? c[1] : c[0]); }
__device__ __forceinline__ float sel22(const float (&c0)[4], const float (&c1)[4], int t) {
    return (t & 2) ? ((t & 1) ? c1[2] : c1[0]) : ((t & 1) ? c0[2] : c0[0]);
}

__device__ __forceinline__ float untag(uint32_t u) { return __uint_as_float(u & ~3u); }
__device__ __forceinline__ void clr(float* p) { asm volatile("st.relaxed.gpu.global.b32 [%0], %1;" ::"l"(p), "r"(0) : "memory"); }
__device__ __forceinline__ void pub(float* p, float a, uint32_t tag) {
    asm volatile("red.relaxed.gpu.global.or.b32 [%0], %1;" ::"l"(p), "r"((__float_as_uint(a) & ~3u) | tag) : "memory");
}
template <int OFF>
__device__ __forceinline__ void ldp(uint32_t& u, const float* p, uint32_t tag) {
    asm volatile("{\n.reg .pred p;\n.reg .b32 t;\nlop3.b32 t, %0, %2, 3, 0x28;\nsetp.ne.u32 p, t, 0;\n"
                 "@p ld.relaxed.gpu.global.b32 %0, [%1+%3];\n}" : "+r"(u) : "l"(p), "r"(tag), "n"(OFF) : "memory");
}
template <int N, int STRIDE, int I = 0>
__device__ __forceinline__ void ldp_all(uint32_t (&u)[N], const float* p, uint32_t tag) {
    if constexpr (I < N) { ldp<I * STRIDE * 4>(u[I], p, tag); ldp_all<N, STRIDE, I + 1>(u, p, tag); }
}
template <int N, int STRIDE>
__device__ __forceinline__ void poll(const float* p, uint32_t tag, float (&v)[N]) {
    uint32_t u[N];
#pragma unroll
    for (int i = 0; i < N; i++) u[i] = 0;
    unsigned it = 0;
#pragma unroll 1
    while (true) {
        ldp_all<N, STRIDE>(u, p, tag);
        uint32_t bad = 0;
#pragma unroll
        for (int i = 0; i < N; i++) asm("lop3.b32 %0, %0, %1, %2, 0xf6;" : "+r"(bad) : "r"(u[i]), "r"(tag));
        if (__all_sync(~0u, !(bad & 3))) break;
        if (++it > SPIN_LIMIT) __trap();
    }
#pragma unroll
    for (int i = 0; i < N; i++) v[i] = untag(u[i]);
}
template <int N>
__device__ __forceinline__ float tree_sum(float (&v)[N]) {
#pragma unroll
    for (int s = 1; s < N; s *= 2)
#pragma unroll
        for (int i = 0; i + s < N; i += 2 * s) v[i] += v[i + s];
    return v[0];
}
__device__ __forceinline__ float xadd(float keep, float send, int o) { return keep + __shfl_xor_sync(~0u, send, o); }

__device__ __forceinline__ void sum6_warp(const float (&v)[6], uint32_t st, int warp, int lane) {
    const bool b4 = lane & 16, b3 = lane & 8, b2 = lane & 4;
    const float w0 = xadd(b4 ? v[3] : v[0], b4 ? v[0] : v[3], 16);
    const float w1 = xadd(b4 ? v[4] : v[1], b4 ? v[1] : v[4], 16);
    const float w2 = xadd(b4 ? v[5] : v[2], b4 ? v[2] : v[5], 16);
    const float z0 = xadd(b3 ? w1 : w0, b3 ? w0 : w1, 8);
    const float z1 = xadd(w2, w2, 8);
    float t = xadd(b2 ? z1 : z0, b2 ? z0 : z1, 4);
    t = xadd(t, t, 2);
    t = xadd(t, t, 1);
    if (!(lane & 3)) stsf(st + (lane >> 2) * 192 + warp * 4, t);
}
__device__ __forceinline__ void sum6_total(float (&v)[6], uint32_t st, int lane) {
    const uint32_t row = st + (lane >> 2) * 192;
    float q[4];
    ldsf4(q, row + (lane & 3) * 16);
    const float e = ldsf(row + 64 + (lane & 1) * 4);
    float t = (q[0] + q[1]) + (q[2] + q[3]) + ((lane & 2) ? 0.f : e);
    t = xadd(t, t, 1);
    t = xadd(t, t, 2);
    v[0] = __shfl_sync(~0u, t, 0);  v[1] = __shfl_sync(~0u, t, 8);  v[2] = __shfl_sync(~0u, t, 4);
    v[3] = __shfl_sync(~0u, t, 16); v[4] = __shfl_sync(~0u, t, 24); v[5] = __shfl_sync(~0u, t, 20);
}

#define BAR(i) (bars + (i) * 8)
__device__ __noinline__ void worker(Scratch* __restrict__ sc, uint32_t ttop, unsigned epoch, uint32_t xraw, uint32_t craw,
                                    const __nv_bfloat16* __restrict__ b1, const __nv_bfloat16* __restrict__ b2,
                                    __nv_bfloat16* __restrict__ out) {
    extern __shared__ __align__(1024) unsigned char smem[];
    const uint32_t sb = (uint32_t)__cvta_generic_to_shared(smem);
    const int tid = threadIdx.x, warp = __shfl_sync(~0u, tid >> 5, 0), lane = tid & 31;
    const int cta = blockIdx.x, g = cta >> 3, r = cta & 7;
    const uint32_t bars = sb + OFF_BAR;
    const int gq = lane >> 2, t4 = lane & 3;
    const int ot = wo_tile(cta), ms = mlp_slot(cta);

    if (warp == 19) {
        const int e = 32 * cta + lane;
        if (cta < 72) clr(sc->modF + e);
        const uint32_t tag = 1 + (epoch & 1);
        bar_sync(5, NTHREADS);
        mbar_wait(BAR(G_K + 4));
        if (cta < 72) {
            float v[16];
            poll<16, 8 * 736>(sc->row[0] + mod_pos(1152 + e), tag, v);
            pub(sc->modF + e, bfr(tree_sum(v)), tag);
        }
        __syncwarp();
        bar_sync(3, 512 + 32);
        {
            float m = ldsf(sb + OFF_WMX + lane * 4), l = ldsf(sb + OFF_WSM + lane * 4);
#pragma unroll
            for (int o = 2; o <= 16; o <<= 1) { m = fmaxf(m, __shfl_xor_sync(~0u, m, o)); l += __shfl_xor_sync(~0u, l, o); }
            if (lane < 8) pub(sc->row[cta] + 704 + lane, (lane & 2) ? l : m, tag);
        }
        if (ot >= 0) {
            mbar_wait(BAR(G_V + 8));
            float v[2];
            poll<2, 2>(sc->row[(cta & ~15) + (lane & 15)] + 704 + (lane >> 4), tag, v);
            float mg = v[0];
#pragma unroll
            for (int o = 1; o <= 4; o <<= 1) mg = fmaxf(mg, __shfl_xor_sync(~0u, mg, o));
            const float w = fexp(v[0] - mg);
            float lg = w * v[1];
#pragma unroll
            for (int o = 1; o <= 4; o <<= 1) lg += __shfl_xor_sync(~0u, lg, o);
            stsf(sb + OFF_WGT + lane * 4, w * frcp(lg));
            __syncwarp();
            bar_arrive(4, 512 + 32);
        }
        if (ms < 0) return;
        float pre[6], v[6];
        bar_sync(9, NCONS + 32);
        sum6_total(pre, sb + OFF_ST + 1536, lane);
        bar_sync(6, NCONS + 32);
        sum6_total(v, sb + OFF_ST + 3072, lane);
        constexpr float RN = 1.f / 576.f;
        const float mean = v[0] * RN, mb = bfr(mean);
        const float r1 = ln_rden(v[1] * RN - mean * mean);
        const float m2 = (r1 * (v[2] - mb * pre[0]) + pre[3]) * RN;
        const float e2 = (r1 * (r1 * (v[3] - mb * (2.f * v[4] - mb * pre[1])) + 2.f * (v[5] - mb * pre[2])) + pre[4]) * RN;
        const float r2 = ln_rden(e2 - m2 * m2), r12 = r1 * r2;
        if (lane < 2) stsf2(sb + OFF_COEF + lane * 8, lane ? -r12 * mb : r12, lane ? r2 : -r2 * bfr(m2));
        __syncwarp();
        bar_arrive(10, 128 + 32);
        return;
    }

    float* const odst = sc->partO[8 * t4 + (cta >> 4)] + 64 * ot + (tid >> 2);
    if (tid < 40) {
        const float cin = __uint_as_float(craw << 16);
        stsv(sb + OFF_S, tid, cin * frcp(1.f + fexp(-cin)));
    }
    const float xv = __uint_as_float(xraw << 16);
    {
        float v[6] = {xv, xv * xv, 0.f, 0.f, 0.f, 0.f};
        sum6_warp(v, sb + OFF_ST, warp, lane);
        bar_sync(1, NCONS);
        sum6_total(v, sb + OFF_ST, lane);
        const float mean = v[0] * (1.f / 576.f);
        stsf(sb + OFF_XN + tid * 4, bfr(bfr(xv - bfr(mean)) * ln_rden(v[1] * (1.f / 576.f) - mean * mean)));
    }
    const uint32_t tag = 1 + (epoch & 1);
    bar_sync(5, NTHREADS);
    const int mi = lane >> 3, l7 = lane & 7;
    const int krw = l7 + ((lane >> 4) << 3);

    {
        uint32_t b[4];
        lds128(b, sb + OFF_S + t4 * 16);
        const uint32_t bt = lds32(sb + OFF_S + 64 + t4 * 16);
#pragma unroll 1
        for (int tl = warp; tl < (r < 6 ? 28 : 24); tl += warp < 8 ? 28 : (tl < 18 ? 10 : 28)) {
            mbar_wait(BAR(G_M + (tl >= 12)));
            const int r0 = (tl >> 2) * 36, ch = 2 * (tl & 3) + (mi & 1), ra = r0 + krw, rb = r0 + 32 + (l7 & 3);
            uint32_t a0[4], a1[4], a2, a3;
            ldsm4t(a0, sb + OFF_M + ra * 128 + ((ch ^ (ra & 7)) << 4));
            ldsm4t(a1, sb + OFF_M + ra * 128 + ((ch ^ (ra & 7)) << 4) + 2048);
            ldsm2t(a2, a3, sb + OFF_M + rb * 128 + ((ch ^ (rb & 7)) << 4));
            float c[4] = {0.f, 0.f, 0.f, 0.f};
            mma16(c, a0, b[0], b[1]);
            mma16(c, a1, b[2], b[3]);
            mma8(c, a2, a3, bt);
            if (t4 < 2) pub(sc->row[cta] + tl * 16 + t4 * 8 + gq, t4 ? c[2] : c[0], tag);
        }
    }
    if (warp >= 16) {
        __syncwarp();
        if (lane == 0) mbar_arrive(BAR(E_B));
        mbar_wait(BAR(G_K + 15));
    } else {
        if (warp < 5) {
            float v[16];
            poll<16, 8 * 736>(sc->row[0] + mod_pos((tid & 1) * 576 + 72 * r + min(tid >> 1, 71)), tag, v);
            const float s = bfr(tree_sum(v));
            const float ca = __shfl_xor_sync(~0u, s, 1);
            if (tid < 144 && !(tid & 1))
                stsv(sb + OFF_H, tid >> 1, bfr(ldsf(sb + OFF_XN + (72 * r + (tid >> 1)) * 4) * bfr(1.f + ca)) + s);
        }
        {
            uint32_t a[4][4], a4, a5;
            const uint32_t base = sb + OFF_WQ + (warp >> 2) * 3072 + l7 * 128 + (((2 * (warp & 3) + (mi & 1)) ^ l7) << 4);
            const bool up = lane & 16;
            mbar_wait(BAR(G_WQ));
            ldsm4t(a[0], base + (up ? 1024 : 0));
            mbar_wait(BAR(G_WQ + 1));
            ldsm4t(a[1], base + (up ? 12288 : 2048));
            ldsm4t(a[2], base + (up ? 12288 + 2048 : 12288 + 1024));
            mbar_wait(BAR(G_WQ + 2));
            ldsm4t(a[3], base + (up ? 24576 + 1024 : 24576));
            ldsm2t(a4, a5, base + 24576 + 2048);
            bar_sync(2, 512);
            uint32_t b0[4], b1r[4];
            lds128(b0, sb + OFF_H + t4 * 16);
            lds128(b1r, sb + OFF_H + 64 + t4 * 16);
            const uint32_t bt = lds32(sb + OFF_H + 128 + t4 * 16);
            float c0[4] = {0.f, 0.f, 0.f, 0.f}, c1[4] = {0.f, 0.f, 0.f, 0.f};
            mma16(c0, a[0], b0[0], b0[1]);
            mma16(c1, a[1], b0[2], b0[3]);
            mma16(c0, a[2], b1r[0], b1r[1]);
            mma16(c1, a[3], b1r[2], b1r[3]);
            mma8(c0, a4, a5, bt);
            if (t4 < 2) pub(sc->row[cta] + 448 + warp * 16 + t4 * 8 + gq, t4 ? c0[2] + c1[2] : c0[0] + c1[0], tag);
            if (lane == 0) mbar_arrive(BAR(E_B));
        }
        if (warp < 8) {
            float v[8];
            poll<8, 736>(sc->row[g * 8] + 448 + tid, tag, v);
            stsv(sb + OFF_Q, tid, tree_sum(v));
        }
        bar_sync(2, 512);
        float sco[2];
        {
            uint32_t qb[4][4];
#pragma unroll
            for (int i = 0; i < 4; i++) lds128(qb[i], sb + OFF_Q + (gq & 1) * 256 + i * 64 + t4 * 16);
            mbar_wait(BAR(G_K + warp));
#pragma unroll
            for (int u = 0; u < 2; u++) {
                const uint32_t base = sb + OFF_K + warp * 8192 + (u * 16 + (lane & 15)) * 128;
                float c0[4] = {0.f, 0.f, 0.f, 0.f}, c1[4] = {0.f, 0.f, 0.f, 0.f};
#pragma unroll
                for (int ks = 0; ks < 4; ks++) {
                    const int sw = ((2 * ks + (lane >> 4)) ^ l7) << 4;
                    uint32_t a[4], a2[4];
                    ldsm4(a, base + sw);
                    ldsm4(a2, base + 4096 + sw);
                    mma16(c0, a, qb[ks >> 1][2 * (ks & 1)], qb[ks >> 1][2 * (ks & 1) + 1]);
                    mma16(c1, a2, qb[2 + (ks >> 1)][2 * (ks & 1)], qb[2 + (ks >> 1)][2 * (ks & 1) + 1]);
                }
                sco[u] = bfr(bfr(sel4(c0, t4) + sel4(c1, t4)) * 0.08838834764831845f);
            }
            float mx = fmaxf(sco[0], sco[1]);
#pragma unroll
            for (int o = 2; o <= 16; o <<= 1) mx = fmaxf(mx, __shfl_xor_sync(~0u, mx, o));
            if (lane < 2) stsf(sb + OFF_WMX + (warp * 2 + lane) * 4, mx);
            if (lane == 0) mbar_arrive(BAR(E_S));
        }
        bar_sync(2, 512);
        {
            float m = ldsf(sb + OFF_WMX + lane * 4);
#pragma unroll
            for (int o = 2; o <= 16; o <<= 1) m = fmaxf(m, __shfl_xor_sync(~0u, m, o));
            const float p0 = fexp(sco[0] - m), p1 = fexp(sco[1] - m);
            const int key = warp * 32 + gq + ((t4 & 2) << 2);
            stsv(sb + OFF_P + (t4 & 1) * 1024, key, p0);
            stsv(sb + OFF_P + (t4 & 1) * 1024, key + 16, p1);
            float l = p0 + p1;
#pragma unroll
            for (int o = 2; o <= 16; o <<= 1) l += __shfl_xor_sync(~0u, l, o);
            if (lane < 2) stsf(sb + OFF_WSM + (warp * 2 + lane) * 4, l);
        }
        bar_sync(3, 512 + 32);
    }
    float* const adst = sc->partA[cta] + warp * 32 + (t4 & 1) * 16 + gq + ((t4 & 2) << 2);
    if (tid < 256) { clr(adst); if (ot >= 0) clr(odst); }
    float b2c = 0.f, b1v = 0.f;
    if (ms >= 0) {
        if (tid < 128) b1v = ldbf(b1 + 64 * ms + (tid >> 1));
        if (warp == (ms >> 2)) b2c = ldbf(b2 + tid);
    }
    float gav = 0.f, sv = 0.f, cv = 0.f, gbv = 0.f;
    if (ms >= 0) {
        float v[4];
        poll<4, 576>(sc->modF + tid, tag, v);
        gav = v[0]; sv = v[1]; cv = bfr(1.f + v[2]); gbv = v[3];
        const float pre[6] = {cv, cv * cv, cv * sv, sv, sv * sv, 0.f};
        sum6_warp(pre, sb + OFF_ST + 1536, warp, lane);
        __syncwarp();
        bar_arrive(9, NCONS + 32);
    }
    if (warp < 8) {
        float c0[4] = {0.f, 0.f, 0.f, 0.f}, c1[4] = {0.f, 0.f, 0.f, 0.f};
        const uint32_t voff = sb + (warp >> 2) * 4096 + krw * 128 + (((2 * (warp & 3) + (mi & 1)) ^ l7) << 4);
        const uint32_t vplain = sb + OFF_VA + krw * 256 + warp * 32 + (mi & 1) * 16;
        const uint32_t pa = sb + OFF_P + (gq & 1) * 1024 + t4 * 16;
#pragma unroll 1
        for (int ck = 0; ck < 16; ck++) {
            const uint32_t src = ck * 8192 + (ck < 2 ? vplain : voff + (ck < 10 ? OFF_VB - 2 * 8192 : OFF_VC - 10 * 8192));
            uint32_t pb[4], a[4], a2[4];
            lds128(pb, pa + ck * 64);
            mbar_wait(BAR(G_V + max(ck, 1)));
            if (ck == 10 && lane == 0) mbar_arrive(BAR(E_V));
            ldsm4t(a, src);
            ldsm4t(a2, src + (ck < 2 ? 4096 : 2048));
            mma16(c0, a, pb[0], pb[1]);
            mma16(c1, a2, pb[2], pb[3]);
        }
        pub(adst, sel4(c0, t4) + sel4(c1, t4), tag);
        if (lane == 0) mbar_arrive(BAR(E_P));
    }
    const uint32_t swz = ((mi & 1) ^ l7) << 4;
    if (warp < 16 && ot >= 0) {
        uint32_t a[8][4], b[4];
        float wt[2][4], v[8];
        bar_sync(4, 512 + 32);
        ldsf4(wt[0], sb + OFF_WGT + (lane & 16) * 4 + (warp & 8) * 4);
        ldsf4(wt[1], sb + OFF_WGT + (lane & 16) * 4 + (warp & 8) * 4 + 16);
        const uint32_t base = sb + OFF_WO + (warp >> 2) * 16384 + ((warp & 3) * 16 + krw) * 128 + swz;
#define LOAD_WO() _Pragma("unroll") for (int i = 0; i < 8; i++) ldsm4t(a[i], (base + (i & 1) * 8192) ^ ((i >> 1) << 5))
        mbar_wait(BAR(G_V + 15));
        while ((int)(gtime() - ttop) < T_A) {}
        const uint32_t wobar = BAR(G_WO + (warp >> 2));
        bool rdy = false;
        {
            uint32_t u[8] = {0, 0, 0, 0, 0, 0, 0, 0};
            unsigned it = 0;
#pragma unroll 1
            while (true) {
                ldp_all<8, 256>(u, sc->partA[(cta & ~15) + (warp & 8)] + (warp & 7) * 32 + lane, tag);
                if (!rdy && mbar_test(wobar)) { LOAD_WO(); rdy = true; }
                uint32_t bad = 0;
#pragma unroll
                for (int i = 0; i < 8; i++) asm("lop3.b32 %0, %0, %1, %2, 0xf6;" : "+r"(bad) : "r"(u[i]), "r"(tag));
                if (__all_sync(~0u, !(bad & 3))) break;
                if (++it > SPIN_LIMIT) __trap();
            }
            if (!rdy && mbar_test(wobar)) { LOAD_WO(); rdy = true; }
#pragma unroll
            for (int i = 0; i < 8; i++) v[i] = untag(u[i]) * wt[i >> 2][i & 3];
        }
        const uint32_t ou = __float_as_uint(bfr(tree_sum(v)));
        const uint32_t pr = (ou >> 16) | __shfl_down_sync(~0u, ou, 1);
#pragma unroll
        for (int j = 0; j < 4; j++) b[j] = __shfl_sync(~0u, pr, 8 * j + 2 * t4);
        if (!rdy) { mbar_wait(wobar); LOAD_WO(); }
        float c[4][4];
#pragma unroll
        for (int i = 0; i < 4; i++) { c[i][0] = c[i][1] = c[i][2] = c[i][3] = 0.f; mma16(c[i], a[2 * i], b[0], b[1]); }
#pragma unroll
        for (int i = 0; i < 4; i++) mma16(c[i], a[2 * i + 1], b[2], b[3]);
        const uint32_t red = sb + OFF_REDO + (warp * 72 + t4 * 8 + gq) * 4;
        stsf(red, sel22(c[0], c[1], t4));
        stsf(red + 128, sel22(c[2], c[3], t4));
    }
    bar_sync(1, NCONS);
    if (warp < 8 && ot >= 0) {
        float v[4];
#pragma unroll
        for (int i = 0; i < 4; i++) v[i] = ldsf(sb + OFF_REDO + ((4 * i + t4) * 72 + (tid >> 2)) * 4);
        float os = tree_sum(v);
        os = xadd(os, os, 1);
        os = xadd(os, os, 2);
        pub(odst, os, tag);
    }
    if (ms < 0) return;
    const uint32_t fb = sb + OFF_FB + warp * 320 + fpos(lane) * 2;
    sts16(fb + 128, __float_as_uint(cv) >> 16);
    sts16(fb + 192, __float_as_uint(sv) >> 16);
    sts16(fb + 256, 0x3f80);
    float* const fdst = sc->row[mlp_cta(warp * 4 + t4)] + ms * 8 + gq;
    float a;
    {
        uint32_t w[8][4], b[4];
        const uint32_t w1bar = BAR(G_W1 + warp / 3);
        bool w1rdy = false;
#define LOAD_W1() _Pragma("unroll") for (int i = 0; i < 8; i++) \
            ldsm4t(w[i], (sb + OFF_W1 + (warp * 32 + (i & 1) * 16 + krw) * 128 + swz) ^ ((i >> 1) << 5))
        {
            uint32_t u[8] = {0, 0, 0, 0, 0, 0, 0, 0};
            unsigned it = 0;
#pragma unroll 1
            while (true) {
                if ((int)(gtime() - ttop) >= T_X) ldp_all<8, 576>(u, sc->partO[8 * (ms & (OREP - 1))] + tid, tag);
                if (!w1rdy && mbar_test(w1bar)) { LOAD_W1(); w1rdy = true; }
                uint32_t bad = 0;
#pragma unroll
                for (int i = 0; i < 8; i++) asm("lop3.b32 %0, %0, %1, %2, 0xf6;" : "+r"(bad) : "r"(u[i]), "r"(tag));
                if (__all_sync(~0u, !(bad & 3))) break;
                if (++it > SPIN_LIMIT) __trap();
            }
            if (!w1rdy && mbar_test(w1bar)) { LOAD_W1(); w1rdy = true; }
            float v[8];
#pragma unroll
            for (int i = 0; i < 8; i++) v[i] = untag(u[i]);
            a = bfr(xv + bfr(gav * bfr(tree_sum(v))));
        }
        const float ac = a * cv, hi = bfr(ac);
        sts16(fb, __float_as_uint(hi) >> 16);
        sts16(fb + 64, __float_as_uint(ac - hi) >> 16);
        __syncwarp();
        lds128(b, sb + OFF_FB + warp * 320 + min(gq, 4) * 64 + t4 * 16);
        const float v[6] = {a, a * a, ac, ac * ac, ac * cv, ac * sv};
        sum6_warp(v, sb + OFF_ST + 3072, warp, lane);
        __syncwarp();
        bar_arrive(6, NCONS + 32);
        if (!w1rdy) { mbar_wait(w1bar); LOAD_W1(); }
        float c[4][4];
#pragma unroll
        for (int i = 0; i < 4; i++) { c[i][0] = c[i][1] = c[i][2] = c[i][3] = 0.f; mma16(c[i], w[2 * i], b[0], b[1]); }
#pragma unroll
        for (int i = 0; i < 4; i++) mma16(c[i], w[2 * i + 1], b[2], b[3]);
        const uint32_t red = sb + OFF_RED + warp * 1024 + gq * 16 + t4 * 8;
#pragma unroll
        for (int j = 0; j < 8; j++) {
            const float e0 = c[j >> 1][2 * (j & 1)], e1 = c[j >> 1][2 * (j & 1) + 1];
            const float one = __shfl_down_sync(~0u, e0, 2);
            if (t4 < 2) stsf2(red + j * 128, t4 ? e0 : e0 + e1, t4 ? e1 : one);
        }
        __syncwarp();
        const uint32_t woff = sb + (warp >> 1) * 1024 + l7 * 128 + (swz ^ ((warp & 1) << 6));
        const bool up = lane & 16;
#define LOAD_W2(k, lo, hi) do { mbar_wait(BAR(G_W2 + (k))); const uint32_t ad = woff + (up ? (hi) : (lo)); \
                                ldsm4t(w[2 * (k)], ad); ldsm4t(w[2 * (k) + 1], ad ^ 32); } while (0)
        if (warp >= 4) {
            bar_arrive(1, NCONS);
        } else {
            bar_sync(1, NCONS);
            float v0[18], v1[18], k0, k1;
#pragma unroll
            for (int i = 0; i < 18; i++) ldsf2(v0[i], v1[i], sb + OFF_RED + i * 1024 + tid * 8);
            const float s0 = tree_sum(v0), s1 = tree_sum(v1);
            bar_sync(10, 128 + 32);
            ldsf2(k0, k1, sb + OFF_COEF + (lane & 1) * 8);
            float u = k0 * s0 + k1 * s1;
            u = xadd(u, u, 1);
            u = bfr(bfr(u) + b1v);
            const float z2 = 1.5957691216057308f * (u + 0.044715f * u * u * u);
            u *= frcp(1.f + fexp(-z2));
            if (!(lane & 1)) stsv(sb + OFF_HH, tid >> 1, u);
            __syncwarp();
            if (lane == 0) mbar_arrive(BAR(R_HH));
        }
        LOAD_W2(0, OFF_W2A, OFF_W2A + 9216);
        LOAD_W2(1, OFF_W2A + 2 * 9216, OFF_W2B);
        mbar_wait(BAR(R_HH));
        uint32_t b2r[4];
        lds128(b, sb + OFF_HH + t4 * 16);
        lds128(b2r, sb + OFF_HH + 64 + t4 * 16);
        float c0[4] = {0.f, 0.f, 0.f, 0.f}, c1[4] = {0.f, 0.f, 0.f, 0.f}, c2[4] = {0.f, 0.f, 0.f, 0.f};
        mma16(c0, w[0], b[0], b[1]);
        mma16(c1, w[1], b[0], b[1]);
        mma16(c0, w[2], b[2], b[3]);
        mma16(c1, w[3], b[2], b[3]);
        LOAD_W2(2, OFF_W2B + 9216, OFF_W2B + 2 * 9216);
        mma16(c0, w[4], b2r[0], b2r[1]);
        mma16(c1, w[5], b2r[0], b2r[1]);
        const uint32_t wo8 = (woff + OFF_W2B + 3 * 9216) ^ ((lane & 16) << 1);
        mbar_wait(BAR(G_W2 + 3));
        ldsm4t(w[6], wo8);
        mma16(c2, w[6], (gq & 1) ? 0u : b2r[2], (gq & 1) ? b2r[2] : 0u);
        const float part = sel22(c0, c1, t4);
        mbar_wait(BAR(G_W2 + 4));
        ldsm4t(w[7], wo8 + 9216);
        mma16(c2, w[7], (gq & 1) ? 0u : b2r[3], (gq & 1) ? b2r[3] : 0u);
        const float res = part + ((t4 & 2) ? ((t4 & 1) ? c2[3] : c2[1]) : ((t4 & 1) ? c2[2] : c2[0]));
        asm volatile("st.relaxed.gpu.global.b32 [%0], %1;" ::"l"(fdst), "r"(__float_as_uint(res) | 3u) : "memory");
    }
    {
        while ((int)(gtime() - ttop) < T_F) {}
        uint32_t u0;
        unsigned it = 0;
#pragma unroll 1
        while (true) {
            asm volatile("ld.relaxed.gpu.global.b32 %0, [%1];" : "=r"(u0) : "l"(sc->row[cta] + tid) : "memory");
            if (__all_sync(~0u, (u0 & 3) == 3)) break;
            if (++it > SPIN_LIMIT) __trap();
        }
        stsf(sb + OFF_OWN + (lane * 20 + warp) * 4, untag(u0));
    }
    if (warp != (ms >> 2)) { bar_arrive(8, NCONS); return; }
    bar_sync(8, NCONS);
    float q[4][4], e0, e1;
#pragma unroll
    for (int i = 0; i < 4; i++) ldsf4(q[i], sb + OFF_OWN + lane * 80 + i * 16);
    ldsf2(e0, e1, sb + OFF_OWN + lane * 80 + 64);
    float k = (((q[0][0] + q[0][1]) + (q[0][2] + q[0][3])) + ((q[1][0] + q[1][1]) + (q[1][2] + q[1][3]))) +
              (((q[2][0] + q[2][1]) + (q[2][2] + q[2][3])) + ((q[3][0] + q[3][1]) + (q[3][2] + q[3][3]))) + (e0 + e1);
    k = xadd(k, k, 8);
    k = xadd(k, k, 16);
    if ((lane >> 3) == (ms & 3)) reinterpret_cast<unsigned short*>(out)[tid] = (unsigned short)pack2(a + bfr(gbv * bfr(bfr(k) + b2c)), 0.f);
    if (tid == 0 && cta == 0) asm volatile("st.relaxed.gpu.global.u32 [%0], %1;" ::"l"(&sc->epoch), "r"(epoch + 1) : "memory");
}

__global__ void __launch_bounds__(NTHREADS, 1)
fused_block_kernel(const unsigned char* __restrict__ vwin, Scratch* __restrict__ sc,
                   const __nv_bfloat16* __restrict__ x_in, const __nv_bfloat16* __restrict__ c_in,
                   const __nv_bfloat16* __restrict__ b1, const __nv_bfloat16* __restrict__ b2,
                   __nv_bfloat16* __restrict__ out, const __grid_constant__ Params prm) {
    const uint32_t ttop = gtime();
    extern __shared__ __align__(1024) unsigned char smem[];
    const int cta = blockIdx.x, g = cta >> 3, r = cta & 7;
    uint64_t pf;
    asm volatile("createpolicy.fractional.L2::evict_first.b64 %0, 1.0;" : "=l"(pf));
    const unsigned char* vsrc = vwin + ((size_t)g << 23) + (r << 14);
    if (threadIdx.x == 0) asm volatile("cp.async.bulk.prefetch.L2.global.L2::cache_hint [%0], %1, %2;" ::"l"(vsrc), "r"(16384), "l"(pf) : "memory");
    const uint32_t sb = (uint32_t)__cvta_generic_to_shared(smem);
    const uint32_t bars = sb + OFF_BAR;
    if (threadIdx.x == 0) {
        mbar_init(BAR(G_V + 1), 1);
        asm volatile("fence.mbarrier_init.release.cluster;" ::: "memory");
        mbar_expect(BAR(G_V + 1), 16384);
        asm volatile("cp.async.bulk.shared::cluster.global.mbarrier::complete_tx::bytes.L2::cache_hint [%0], [%1], %2, [%3], %4;"
                     ::"r"(sb + OFF_VA), "l"(vsrc), "r"(16384), "r"(BAR(G_V + 1)), "l"(pf) : "memory");
    }
    const int tid = threadIdx.x, warp = __shfl_sync(~0u, tid >> 5, 0);
    if (warp != 18) {
        unsigned epoch;
        asm volatile("ld.relaxed.gpu.global.u32 %0, [%1];" : "=r"(epoch) : "l"(&sc->epoch) : "memory");
        uint32_t xv = 0, cin = 0;
        if (tid < NCONS) asm volatile("ld.global.u16 %0, [%1];" : "=r"(xv) : "l"(x_in + tid) : "memory");
        if (tid < 36) asm volatile("ld.global.u16 %0, [%1];" : "=r"(cin) : "l"(c_in + 36 * g + tid) : "memory");
        if (tid < 184)
            asm volatile("st.relaxed.gpu.global.v4.b32 [%0], {%1,%1,%1,%1};" ::"l"(sc->row[cta] + tid * 4), "r"(0) : "memory");
        worker(sc, ttop, epoch, xv, cin, b1, b2, out);
        return;
    }
    {
        const int krow = g * SK + (SK - WIN) + 64 * r;
        const uint32_t t0 = ttop + (cta - 64) * 5 / 2;
        const bool el = elect();
        if (el) asm volatile("prefetch.tensormap [%0];" ::"l"(&prm.m[0]) : "memory");
#define LOAD(n, dst, map, c0, c1, c2) do { if (el) tma3(sb + (dst), &prm.m[map], c0, c1, c2, BAR(n), pf); } while (0)
#define EXPECT(n, bytes) do { if (el) mbar_expect(BAR(n), bytes); } while (0)
#define AT(t) do { } while ((int)(gtime() - t0) < (int)(t))
        if (el) {
            mbar_init(BAR(G_M), 1);
            mbar_init(BAR(G_M + 1), 1);
            asm volatile("fence.mbarrier_init.release.cluster;" ::: "memory");
            mbar_expect(BAR(G_M), 3 * 4608);
            mbar_expect(BAR(G_M + 1), 4 * 4608);
#pragma unroll
            for (int i = 0; i < 7; i++) tma3(sb + OFF_M + i * 4608, &prm.m[0], 0, 36 * g, r + 8 * i, BAR(G_M + (i >= 3)), pf);
        }
        if (el) {
            asm volatile("prefetch.tensormap [%0];" ::"l"(&prm.m[1]) : "memory");
            asm volatile("prefetch.tensormap [%0];" ::"l"(&prm.m[2]) : "memory");
#pragma unroll
            for (int i = 2; i < NFULL; i++) if (i != G_V && i != G_V + 1) mbar_init(BAR(i), 1);
            mbar_init(BAR(E_B), 18);
            mbar_init(BAR(E_S), 16);
            mbar_init(BAR(E_V), 8);
            mbar_init(BAR(E_P), 8);
            mbar_init(BAR(R_HH), 4);
            asm volatile("fence.mbarrier_init.release.cluster;" ::: "memory");
        }
        __syncwarp();
        bar_arrive(5, NTHREADS);
#pragma unroll 1
        for (int i = 0; i < 3; i++) {
            EXPECT(G_WQ + i, 12288);
            AT(T_WQ + i * D_WQ);
            LOAD(G_WQ + i, OFF_WQ + i * 12288, 1, 0, 72 * r + 24 * i, 4 * g);
        }
        if (el) {
#pragma unroll
            for (int i = 3; i < 7; i++) asm volatile("prefetch.tensormap [%0];" ::"l"(&prm.m[i]) : "memory");
        }
#pragma unroll 1
        for (int n = 0; n < 30; n++) {
            const int i = n < 16 ? n : n + 2, dep = n - CAPN;
            EXPECT(G_K + i, 8192);
            if (i == 18) mbar_wait(BAR(E_B));
            if (i == 26) mbar_wait(BAR(E_S));
            if (dep >= 0) mbar_wait(BAR(G_K + (dep < 16 ? dep : dep + 2)));
            const int dst = i * 8192 + (i < 16 ? OFF_K : (i < 26 ? OFF_VB - 18 * 8192 : OFF_VC - 26 * 8192));
            AT(T_KV + n * D_KV);
            LOAD(G_K + i, dst, 2 + (i >> 4), 0, krow + 256 * (i & 14) + 32 * (i & 1), 0);
        }
        const int ot = wo_tile(cta), ms = mlp_slot(cta);
        if (ot >= 0) {
#pragma unroll 1
            for (int i = 0; i < 8; i++) {
                if (!(i & 1)) EXPECT(G_WO + (i >> 1), 16384);
                AT(T_WO + i * D_WO);
                LOAD(G_WO + (i >> 1), OFF_WO + i * 8192, 4, 64 * ot, 512 * (cta >> 4) + 256 * (i >> 2) + 128 * (i & 1) + 32 * (i & 2), 0);
            }
        }
        if (ms < 0) return;
        mbar_wait(BAR(E_V));
#pragma unroll 1
        for (int i = 0; i < 12; i++) {
            if (!(i & 1)) EXPECT(G_W1 + (i >> 1), 12288);
            AT(T_W1 + i * D_W1);
            LOAD(G_W1 + (i >> 1), OFF_W1 + i * 6144, 5, 64 * ms, 48 * i, 0);
        }
        EXPECT(G_W2, 18432); EXPECT(G_W2 + 1, 18432); EXPECT(G_W2 + 2, 18432); EXPECT(G_W2 + 3, 9216); EXPECT(G_W2 + 4, 9216);
        mbar_wait(BAR(E_P));
#pragma unroll 1
        for (int i = 0; i < 8; i++) {
            AT(T_W2 + i * D_W2);
            LOAD(G_W2 + (i == 7 ? 4 : i >> 1), i * 9216 + (i < 3 ? OFF_W2A : OFF_W2B - 3 * 9216), 6, 0, 64 * ms + 8 * i, 0);
        }
        return;
    }
#undef BAR
}

typedef CUresult (*EncodeFn)(CUtensorMap*, CUtensorMapDataType, cuuint32_t, void*, const cuuint64_t*, const cuuint64_t*,
                             const cuuint32_t*, const cuuint32_t*, CUtensorMapInterleave, CUtensorMapSwizzle,
                             CUtensorMapL2promotion, CUtensorMapFloatOOBfill);

void make_map(EncodeFn enc, CUtensorMap* m, const void* ptr, cuuint64_t d0, cuuint64_t d1, cuuint64_t d2, cuuint64_t s1,
              cuuint64_t s2, cuuint32_t b0, cuuint32_t b1, cuuint32_t b2, bool swz, bool p256 = true) {
    const cuuint64_t dims[3] = {d0, d1, d2}, str[2] = {s1, s2};
    const cuuint32_t box[3] = {b0, b1, b2}, es[3] = {1, 1, 1};
    enc(m, CU_TENSOR_MAP_DATA_TYPE_BFLOAT16, 3, const_cast<void*>(ptr), dims, str, box, es, CU_TENSOR_MAP_INTERLEAVE_NONE,
        swz ? CU_TENSOR_MAP_SWIZZLE_128B : CU_TENSOR_MAP_SWIZZLE_NONE,
        swz && p256 ? CU_TENSOR_MAP_L2_PROMOTION_L2_256B : CU_TENSOR_MAP_L2_PROMOTION_L2_128B, CU_TENSOR_MAP_FLOAT_OOB_FILL_NONE);
}

}

extern "C" void kernel_launch(void* const* d_in, const int* in_sizes, int n_in, void* d_out, int out_size) {
    (void)in_sizes; (void)n_in; (void)out_size;
    static EncodeFn enc = nullptr;
    static Scratch* scr = nullptr;
    if (!enc) {
        void* fn = nullptr;
        cudaDriverEntryPointQueryResult st;
        cudaGetDriverEntryPoint("cuTensorMapEncodeTiled", &fn, cudaEnableDefault, &st);
        enc = (EncodeFn)fn;
        cudaGetSymbolAddress((void**)&scr, g_scratch);
        cudaFuncSetAttribute(fused_block_kernel, cudaFuncAttributeMaxDynamicSharedMemorySize, SMEM_BYTES);
    }
    Params p;
    make_map(enc, &p.m[0], d_in[11], 64, 576, 54, 3456 * 2, 128, 64, 36, 1, true, false);
    make_map(enc, &p.m[1], d_in[3], 64, 576, 64, 4096 * 2, 128, 64, 24, 4, true);
    make_map(enc, &p.m[2], d_in[1], 64, 16ull * SK, 2, 256, 128, 64, 32, 2, true);
    make_map(enc, &p.m[3], d_in[2], 64, 16ull * SK, 2, 256, 128, 64, 32, 2, true);
    make_map(enc, &p.m[4], d_in[4], 576, 4096, 1, 576 * 2, 576 * 2 * 4096, 64, 64, 1, true, false);
    make_map(enc, &p.m[5], d_in[6], FF, 576, 1, FF * 2, FF * 2 * 576, 64, 48, 1, true, false);
    make_map(enc, &p.m[6], d_in[8], 64, FF, 9, 576 * 2, 128, 64, 8, 9, true);
    fused_block_kernel<<<NCTA, NTHREADS, SMEM_BYTES>>>((const unsigned char*)d_in[2] + (size_t)(SK - WIN) * 256, scr, (const __nv_bfloat16*)d_in[0],
                                                        (const __nv_bfloat16*)d_in[10], (const __nv_bfloat16*)d_in[7],
                                                        (const __nv_bfloat16*)d_in[9], (__nv_bfloat16*)d_out, p);
}
```
